```python
import torch

def _softmax(x, axis=-1):
    return torch.softmax(x, dim=axis)
def _gelu(x):
    return torch.nn.functional.gelu(x, approximate="tanh")
def _silu(x):
    return torch.nn.functional.silu(x)
def _sigmoid(x):
    return torch.sigmoid(x)
def _layernorm(x, axis=-1, eps=1e-5):
    m = x.mean(dim=axis, keepdim=True)
    v = x.var(dim=axis, keepdim=True, unbiased=False)
    return (x - m) / torch.sqrt(v + eps)
def _scatter_add(tgt, idx, src, axis=0):
    return tgt.clone().index_add_(axis, idx, src)
def _segment_sum(src, seg, n):
    out = torch.zeros((n,) + src.shape[1:], dtype=src.dtype)
    return out.index_add_(0, seg, src)
def _pad(x, pw):
    flat = tuple(v for pair in reversed(pw) for v in pair)
    return torch.nn.functional.pad(x, flat)

kernel_name = 'concat_heads__mha_block_cached__mha_block_cached__near_ridge'

def setup_inputs():

    _w = (lambda a: (lambda t: t.to(torch.bfloat16) if t.is_floating_point() else t)(torch.as_tensor(a)))
    def _A_setup():
        B, Sq, D = 16, 32, 1024
        H, Sk, Dh = 32, 32, 128
        return {
            "x": _w((lambda *s: torch.randn(*s, dtype=torch.bfloat16) * 0.8)(B, Sq, D)),
            "k_cache": _w((lambda *s: torch.randn(*s, dtype=torch.bfloat16) * 0.8)(B, H, Sk, Dh)),
            "v_cache": _w((lambda *s: torch.randn(*s, dtype=torch.bfloat16) * 0.05)(B, H, Sk, Dh)),
            "wq": _w((lambda *s: torch.randn(*s, dtype=torch.bfloat16) * 0.8)(D, H * Dh) * (D ** -0.5)),
            "wo": _w((lambda *s: torch.randn(*s, dtype=torch.bfloat16) * 0.05)(H * Dh, D) * ((H * Dh) ** -0.5)),
        }
    _A_in = _A_setup()

    def _B_setup():
        B, Sq, D = 16, 32, 1024
        H, Sk, Dh = 32, 32, 128
        return {
            "x": _w((lambda *s: torch.randn(*s, dtype=torch.bfloat16) * 0.8)(B, Sq, D)),
            "k_cache": _w((lambda *s: torch.randn(*s, dtype=torch.bfloat16) * 0.8)(B, H, Sk, Dh)),
            "v_cache": _w((lambda *s: torch.randn(*s, dtype=torch.bfloat16) * 0.05)(B, H, Sk, Dh)),
            "wq": _w((lambda *s: torch.randn(*s, dtype=torch.bfloat16) * 0.8)(D, H * Dh) * (D ** -0.5)),
            "wo": _w((lambda *s: torch.randn(*s, dtype=torch.bfloat16) * 0.05)(H * Dh, D) * ((H * Dh) ** -0.5)),
        }
    _B_in = _B_setup()

    return {
        "A_x": _A_in["x"],
        "A_k_cache": _A_in["k_cache"],
        "A_v_cache": _A_in["v_cache"],
        "A_wq": _A_in["wq"],
        "A_wo": _A_in["wo"],
        "B_x": _B_in["x"],
        "B_k_cache": _B_in["k_cache"],
        "B_v_cache": _B_in["v_cache"],
        "B_wq": _B_in["wq"],
        "B_wo": _B_in["wo"],
    }

def reference(A_x, A_k_cache, A_v_cache, A_wq, A_wo, B_x, B_k_cache, B_v_cache, B_wq, B_wo):
    def _A_ref(x, k_cache, v_cache, wq, wo):
        B, Sq, D = x.shape
        H, Dh = 32, 128
        q = (lambda x, *d: x.permute(*d))((x @ wq).reshape(B, Sq, H, Dh), 0, 2, 1, 3)
        scores = torch.einsum("bhqd,bhkd->bhqk", q, k_cache) * (Dh ** -0.5)
        p = _softmax(scores, axis=-1)
        o = torch.einsum("bhqk,bhkd->bhqd", p, v_cache)
        return (lambda x, *d: x.permute(*d))(o, 0, 2, 1, 3).reshape(B, Sq, H * Dh) @ wo

    def _B_ref(x, k_cache, v_cache, wq, wo):
        B, Sq, D = x.shape
        H, Dh = 32, 128
        q = (lambda x, *d: x.permute(*d))((x @ wq).reshape(B, Sq, H, Dh), 0, 2, 1, 3)
        scores = torch.einsum("bhqd,bhkd->bhqk", q, k_cache) * (Dh ** -0.5)
        p = _softmax(scores, axis=-1)
        o = torch.einsum("bhqk,bhkd->bhqd", p, v_cache)
        return (lambda x, *d: x.permute(*d))(o, 0, 2, 1, 3).reshape(B, Sq, H * Dh) @ wo

    a = _A_ref(A_x, A_k_cache, A_v_cache, A_wq, A_wo)
    b = _B_ref(B_x, B_k_cache, B_v_cache, B_wq, B_wo)
    return torch.concatenate([a, b], axis=-1)
```

```cpp
#include <cuda_runtime.h>
#include <cuda_bf16.h>
#include <cuda.h>
#include <stdint.h>

namespace {

constexpr int BM = 128, BN = 256, BK = 64;
constexpr int STAGES = 4;
constexpr int A_BYTES = BM * BK * 2;
constexpr int B_BYTES = BK * BN * 2;
constexpr int STAGE_BYTES = A_BYTES + B_BYTES;
constexpr int BOX_BYTES = 64 * 64 * 2;
constexpr int NTHREADS = 384;
constexpr int KTILES = 16;
constexpr int SMEM_BYTES = STAGES * STAGE_BYTES + 1024 + 256;

__device__ __nv_bfloat16 g_o[2 * 512 * 4096];

__device__ __forceinline__ uint32_t smem_u32(const void* p) {
    return (uint32_t)__cvta_generic_to_shared(p);
}
__device__ __forceinline__ void mbar_init(uint32_t bar, uint32_t count) {
    asm volatile("mbarrier.init.shared::cta.b64 [%0], %1;" ::"r"(bar), "r"(count));
}
__device__ __forceinline__ void mbar_expect_tx(uint32_t bar, uint32_t bytes) {
    asm volatile("mbarrier.arrive.expect_tx.shared::cta.b64 _, [%0], %1;" ::"r"(bar), "r"(bytes) : "memory");
}
__device__ __forceinline__ void mbar_arrive(uint32_t bar) {
    asm volatile("mbarrier.arrive.shared::cta.b64 _, [%0];" ::"r"(bar) : "memory");
}
__device__ __forceinline__ void mbar_wait(uint32_t bar, uint32_t parity) {
    asm volatile(
        "{\n"
        ".reg .pred P1;\n"
        "LAB_WAIT:\n"
        "mbarrier.try_wait.parity.shared::cta.b64 P1, [%0], %1;\n"
        "@P1 bra DONE;\n"
        "bra LAB_WAIT;\n"
        "DONE:\n"
        "}\n" ::"r"(bar), "r"(parity) : "memory");
}
__device__ __forceinline__ void tma_load_2d(uint32_t dst, const CUtensorMap* tm, uint32_t bar, int c0, int c1) {
    asm volatile(
        "cp.async.bulk.tensor.2d.shared::cluster.global.mbarrier::complete_tx::bytes [%0], [%1, {%3, %4}], [%2];"
        ::"r"(dst), "l"(tm), "r"(bar), "r"(c0), "r"(c1) : "memory");
}
__device__ __forceinline__ void wgmma_fence() { asm volatile("wgmma.fence.sync.aligned;" ::: "memory"); }
__device__ __forceinline__ void wgmma_commit() { asm volatile("wgmma.commit_group.sync.aligned;" ::: "memory"); }
template <int N>
__device__ __forceinline__ void wgmma_wait() { asm volatile("wgmma.wait_group.sync.aligned %0;" ::"n"(N) : "memory"); }

__device__ __forceinline__ uint64_t make_desc(uint32_t addr, uint32_t lbo, uint32_t sbo) {
    uint64_t d = 0;
    d |= (uint64_t)((addr & 0x3FFFF) >> 4);
    d |= (uint64_t)((lbo >> 4) & 0x3FFF) << 16;
    d |= (uint64_t)((sbo >> 4) & 0x3FFF) << 32;
    d |= (uint64_t)1 << 62;
    return d;
}

__device__ __forceinline__ void wgmma_m64n256k16(float (&d)[128], uint64_t da, uint64_t db, int scale_d) {
    asm volatile(
        "{\n"
        ".reg .pred p;\n"
        "setp.ne.b32 p, %130, 0;\n"
        "wgmma.mma_async.sync.aligned.m64n256k16.f32.bf16.bf16 "
        "{%0, %1, %2, %3, %4, %5, %6, %7, %8, %9, %10, %11, %12, %13, %14, %15, "
        "%16, %17, %18, %19, %20, %21, %22, %23, %24, %25, %26, %27, %28, %29, %30, %31, "
        "%32, %33, %34, %35, %36, %37, %38, %39, %40, %41, %42, %43, %44, %45, %46, %47, "
        "%48, %49, %50, %51, %52, %53, %54, %55, %56, %57, %58, %59, %60, %61, %62, %63, "
        "%64, %65, %66, %67, %68, %69, %70, %71, %72, %73, %74, %75, %76, %77, %78, %79, "
        "%80, %81, %82, %83, %84, %85, %86, %87, %88, %89, %90, %91, %92, %93, %94, %95, "
        "%96, %97, %98, %99, %100, %101, %102, %103, %104, %105, %106, %107, %108, %109, %110, %111, "
        "%112, %113, %114, %115, %116, %117, %118, %119, %120, %121, %122, %123, %124, %125, %126, %127}, "
        "%128, %129, p, 1, 1, 0, 1;\n"
        "}\n"
        : "+f"(d[0]), "+f"(d[1]), "+f"(d[2]), "+f"(d[3]), "+f"(d[4]), "+f"(d[5]), "+f"(d[6]), "+f"(d[7]),
          "+f"(d[8]), "+f"(d[9]), "+f"(d[10]), "+f"(d[11]), "+f"(d[12]), "+f"(d[13]), "+f"(d[14]), "+f"(d[15]),
          "+f"(d[16]), "+f"(d[17]), "+f"(d[18]), "+f"(d[19]), "+f"(d[20]), "+f"(d[21]), "+f"(d[22]), "+f"(d[23]),
          "+f"(d[24]), "+f"(d[25]), "+f"(d[26]), "+f"(d[27]), "+f"(d[28]), "+f"(d[29]), "+f"(d[30]), "+f"(d[31]),
          "+f"(d[32]), "+f"(d[33]), "+f"(d[34]), "+f"(d[35]), "+f"(d[36]), "+f"(d[37]), "+f"(d[38]), "+f"(d[39]),
          "+f"(d[40]), "+f"(d[41]), "+f"(d[42]), "+f"(d[43]), "+f"(d[44]), "+f"(d[45]), "+f"(d[46]), "+f"(d[47]),
          "+f"(d[48]), "+f"(d[49]), "+f"(d[50]), "+f"(d[51]), "+f"(d[52]), "+f"(d[53]), "+f"(d[54]), "+f"(d[55]),
          "+f"(d[56]), "+f"(d[57]), "+f"(d[58]), "+f"(d[59]), "+f"(d[60]), "+f"(d[61]), "+f"(d[62]), "+f"(d[63]),
          "+f"(d[64]), "+f"(d[65]), "+f"(d[66]), "+f"(d[67]), "+f"(d[68]), "+f"(d[69]), "+f"(d[70]), "+f"(d[71]),
          "+f"(d[72]), "+f"(d[73]), "+f"(d[74]), "+f"(d[75]), "+f"(d[76]), "+f"(d[77]), "+f"(d[78]), "+f"(d[79]),
          "+f"(d[80]), "+f"(d[81]), "+f"(d[82]), "+f"(d[83]), "+f"(d[84]), "+f"(d[85]), "+f"(d[86]), "+f"(d[87]),
          "+f"(d[88]), "+f"(d[89]), "+f"(d[90]), "+f"(d[91]), "+f"(d[92]), "+f"(d[93]), "+f"(d[94]), "+f"(d[95]),
          "+f"(d[96]), "+f"(d[97]), "+f"(d[98]), "+f"(d[99]), "+f"(d[100]), "+f"(d[101]), "+f"(d[102]), "+f"(d[103]),
          "+f"(d[104]), "+f"(d[105]), "+f"(d[106]), "+f"(d[107]), "+f"(d[108]), "+f"(d[109]), "+f"(d[110]), "+f"(d[111]),
          "+f"(d[112]), "+f"(d[113]), "+f"(d[114]), "+f"(d[115]), "+f"(d[116]), "+f"(d[117]), "+f"(d[118]), "+f"(d[119]),
          "+f"(d[120]), "+f"(d[121]), "+f"(d[122]), "+f"(d[123]), "+f"(d[124]), "+f"(d[125]), "+f"(d[126]), "+f"(d[127])
        : "l"(da), "l"(db), "r"(scale_d));
}

__device__ __forceinline__ void ldsm_x4(uint32_t addr, uint32_t& r0, uint32_t& r1, uint32_t& r2, uint32_t& r3) {
    asm volatile("ldmatrix.sync.aligned.m8n8.x4.shared.b16 {%0, %1, %2, %3}, [%4];"
                 : "=r"(r0), "=r"(r1), "=r"(r2), "=r"(r3) : "r"(addr));
}
__device__ __forceinline__ void ldsm_x4_t(uint32_t addr, uint32_t& r0, uint32_t& r1, uint32_t& r2, uint32_t& r3) {
    asm volatile("ldmatrix.sync.aligned.m8n8.x4.trans.shared.b16 {%0, %1, %2, %3}, [%4];"
                 : "=r"(r0), "=r"(r1), "=r"(r2), "=r"(r3) : "r"(addr));
}
__device__ __forceinline__ void mma_bf16(float (&c)[4], uint32_t a0, uint32_t a1, uint32_t a2, uint32_t a3,
                                         uint32_t b0, uint32_t b1) {
    asm volatile(
        "mma.sync.aligned.m16n8k16.row.col.f32.bf16.bf16.f32 {%0, %1, %2, %3}, {%4, %5, %6, %7}, {%8, %9}, "
        "{%0, %1, %2, %3};"
        : "+f"(c[0]), "+f"(c[1]), "+f"(c[2]), "+f"(c[3])
        : "r"(a0), "r"(a1), "r"(a2), "r"(a3), "r"(b0), "r"(b1));
}
__device__ __forceinline__ uint32_t pack_bf16(float lo, float hi) {
    __nv_bfloat162 v = __floats2bfloat162_rn(lo, hi);
    return *reinterpret_cast<uint32_t*>(&v);
}
__device__ __forceinline__ float bf16_round(float x) { return __bfloat162float(__float2bfloat16_rn(x)); }

__device__ __forceinline__ void mainloop_consumer(float (&acc)[128], uint32_t smem_base, uint32_t full_bar,
                                                  uint32_t empty_bar, int wg, bool leader) {
#pragma unroll 1
    for (int it = 0; it < KTILES; ++it) {
        const int s = it % STAGES;
        mbar_wait(full_bar + 8 * s, (it / STAGES) & 1);
        const uint32_t a_addr = smem_base + s * STAGE_BYTES + wg * (64 * 128);
        const uint32_t b_addr = smem_base + s * STAGE_BYTES + A_BYTES;
        wgmma_fence();
#pragma unroll
        for (int k = 0; k < 4; ++k) {
            uint64_t da = make_desc(a_addr + k * 32, 16, 1024);
            uint64_t db = make_desc(b_addr + k * 2048, BOX_BYTES, 1024);
            wgmma_m64n256k16(acc, da, db, (it | k) != 0);
        }
        wgmma_commit();
        if (it > 0) {
            wgmma_wait<1>();
            if (leader) mbar_arrive(empty_bar + 8 * ((it - 1) % STAGES));
        }
    }
    wgmma_wait<0>();
    if (leader) mbar_arrive(empty_bar + 8 * ((KTILES - 1) % STAGES));
}

__global__ void __launch_bounds__(NTHREADS, 1)
qproj_attn_kernel(const __grid_constant__ CUtensorMap tmX0, const __grid_constant__ CUtensorMap tmX1,
                  const __grid_constant__ CUtensorMap tmW0, const __grid_constant__ CUtensorMap tmW1,
                  const __grid_constant__ CUtensorMap tmK0, const __grid_constant__ CUtensorMap tmK1,
                  const __grid_constant__ CUtensorMap tmV0, const __grid_constant__ CUtensorMap tmV1) {
    extern __shared__ uint8_t smem_raw[];
    const uint32_t smem_base = (smem_u32(smem_raw) + 1023) & ~1023u;
    const uint32_t full_bar = smem_base + STAGES * STAGE_BYTES;
    const uint32_t empty_bar = full_bar + 8 * STAGES;

    const int idx = blockIdx.x;
    const int blk = idx >> 6;
    const int nt = (idx & 63) >> 2;
    const int mt = idx & 3;
    const int warp = threadIdx.x >> 5;
    const int lane = threadIdx.x & 31;

    if (threadIdx.x == 0) {
        for (int s = 0; s < STAGES; ++s) {
            mbar_init(full_bar + 8 * s, 1);
            mbar_init(empty_bar + 8 * s, 2);
        }
        asm volatile("fence.mbarrier_init.release.cluster;" ::: "memory");
    }
    __syncthreads();

    if (warp >= 8) {
        if (warp == 8 && lane == 0) {
            const CUtensorMap* tmX = blk ? &tmX1 : &tmX0;
            const CUtensorMap* tmW = blk ? &tmW1 : &tmW0;
            const CUtensorMap* tmK = blk ? &tmK1 : &tmK0;
            const CUtensorMap* tmV = blk ? &tmV1 : &tmV0;
            for (int it = 0; it < KTILES; ++it) {
                const int s = it % STAGES;
                mbar_wait(empty_bar + 8 * s, ((it / STAGES) & 1) ^ 1);
                const uint32_t st = smem_base + s * STAGE_BYTES;
                mbar_expect_tx(full_bar + 8 * s, STAGE_BYTES);
                tma_load_2d(st, tmX, full_bar + 8 * s, it * BK, mt * BM);
#pragma unroll
                for (int j = 0; j < 4; ++j)
                    tma_load_2d(st + A_BYTES + j * BOX_BYTES, tmW, full_bar + 8 * s, nt * BN + j * 64, it * BK);
            }
            for (int t = 0; t < 3; ++t) {
                const int it = KTILES + t;
                const int s = it % STAGES;
                mbar_wait(empty_bar + 8 * s, ((it / STAGES) & 1) ^ 1);
                const int nbox = (t < 2) ? 6 : 4;
                mbar_expect_tx(full_bar + 8 * s, nbox * BOX_BYTES);
                for (int j = 0; j < nbox; ++j) {
                    const int e = t * 6 + j;
                    const int kv = e >> 3, bl = (e >> 1) & 3, half = e & 1;
                    const int row0 = ((mt * 4 + bl) * 32 + nt * 2) * 32;
                    tma_load_2d(smem_base + s * STAGE_BYTES + j * BOX_BYTES, kv ? tmV : tmK, full_bar + 8 * s,
                                half * 64, row0);
                }
            }
        }
    } else {
        const int wg = warp >> 2;
        const bool leader = (threadIdx.x & 127) == 0;
        float acc[128];
        mainloop_consumer(acc, smem_base, full_bar, empty_bar, wg, leader);

        uint32_t qf[64];
#pragma unroll
        for (int i = 0; i < 64; ++i) qf[i] = pack_bf16(acc[2 * i], acc[2 * i + 1]);

#pragma unroll
        for (int t = 0; t < 3; ++t) {
            const int it = KTILES + t;
            mbar_wait(full_bar + 8 * (it % STAGES), (it / STAGES) & 1);
        }
        const int bl = wg * 2 + ((warp & 3) >> 1);
        const uint32_t kbase = smem_base + (bl * 2) * BOX_BYTES;
        const uint32_t vbase = smem_base + (8 + bl * 2) * BOX_BYTES;
        const int g = lane >> 2, tq = lane & 3;
        const int row_g = mt * BM + wg * 64 + (warp & 3) * 16 + g;
        __nv_bfloat16* o_ptr = g_o + ((size_t)blk * 512 + row_g) * 4096 + (size_t)nt * 256;

#pragma unroll
        for (int hh = 0; hh < 2; ++hh) {
            float sc[4][4];
#pragma unroll
            for (int n = 0; n < 4; ++n)
#pragma unroll
                for (int c = 0; c < 4; ++c) sc[n][c] = 0.f;
#pragma unroll
            for (int kk = 0; kk < 8; kk += 2) {
                const int chunk = 2 * kk + (lane >> 3);
                const int half = chunk >> 3, c8 = chunk & 7;
#pragma unroll
                for (int n = 0; n < 4; ++n) {
                    const int r = hh * 32 + n * 8 + (lane & 7);
                    const uint32_t addr = kbase + half * BOX_BYTES + r * 128 + ((c8 ^ (r & 7)) << 4);
                    uint32_t b0, b1, b2, b3;
                    ldsm_x4(addr, b0, b1, b2, b3);
                    const int q0 = hh * 32 + kk * 4;
                    mma_bf16(sc[n], qf[q0 + 0], qf[q0 + 1], qf[q0 + 2], qf[q0 + 3], b0, b1);
                    mma_bf16(sc[n], qf[q0 + 4], qf[q0 + 5], qf[q0 + 6], qf[q0 + 7], b2, b3);
                }
            }
            const float scale = 0.08838834764831845f;
            float m0 = -INFINITY, m1 = -INFINITY;
#pragma unroll
            for (int n = 0; n < 4; ++n) {
#pragma unroll
                for (int c = 0; c < 4; ++c) sc[n][c] = bf16_round(bf16_round(sc[n][c]) * scale);
                m0 = fmaxf(m0, fmaxf(sc[n][0], sc[n][1]));
                m1 = fmaxf(m1, fmaxf(sc[n][2], sc[n][3]));
            }
            m0 = fmaxf(m0, __shfl_xor_sync(0xffffffffu, m0, 1));
            m0 = fmaxf(m0, __shfl_xor_sync(0xffffffffu, m0, 2));
            m1 = fmaxf(m1, __shfl_xor_sync(0xffffffffu, m1, 1));
            m1 = fmaxf(m1, __shfl_xor_sync(0xffffffffu, m1, 2));
            float s0 = 0.f, s1 = 0.f;
#pragma unroll
            for (int n = 0; n < 4; ++n) {
                sc[n][0] = __expf(sc[n][0] - m0);
                sc[n][1] = __expf(sc[n][1] - m0);
                sc[n][2] = __expf(sc[n][2] - m1);
                sc[n][3] = __expf(sc[n][3] - m1);
                s0 += sc[n][0] + sc[n][1];
                s1 += sc[n][2] + sc[n][3];
            }
            s0 += __shfl_xor_sync(0xffffffffu, s0, 1);
            s0 += __shfl_xor_sync(0xffffffffu, s0, 2);
            s1 += __shfl_xor_sync(0xffffffffu, s1, 1);
            s1 += __shfl_xor_sync(0xffffffffu, s1, 2);
            const float i0 = 1.f / s0, i1 = 1.f / s1;
            uint32_t pf[2][4];
#pragma unroll
            for (int kk = 0; kk < 2; ++kk) {
                pf[kk][0] = pack_bf16(sc[2 * kk][0] * i0, sc[2 * kk][1] * i0);
                pf[kk][1] = pack_bf16(sc[2 * kk][2] * i1, sc[2 * kk][3] * i1);
                pf[kk][2] = pack_bf16(sc[2 * kk + 1][0] * i0, sc[2 * kk + 1][1] * i0);
                pf[kk][3] = pack_bf16(sc[2 * kk + 1][2] * i1, sc[2 * kk + 1][3] * i1);
            }
#pragma unroll
            for (int n = 0; n < 16; ++n) {
                const int r = hh * 32 + lane;
                const int half = n >> 3, c8 = n & 7;
                const uint32_t addr = vbase + half * BOX_BYTES + r * 128 + ((c8 ^ (r & 7)) << 4);
                uint32_t b0, b1, b2, b3;
                ldsm_x4_t(addr, b0, b1, b2, b3);
                float oc[4] = {0.f, 0.f, 0.f, 0.f};
                mma_bf16(oc, pf[0][0], pf[0][1], pf[0][2], pf[0][3], b0, b1);
                mma_bf16(oc, pf[1][0], pf[1][1], pf[1][2], pf[1][3], b2, b3);
                __nv_bfloat16* p = o_ptr + hh * 128 + n * 8 + tq * 2;
                *reinterpret_cast<uint32_t*>(p) = pack_bf16(oc[0], oc[1]);
                *reinterpret_cast<uint32_t*>(p + 8 * 4096) = pack_bf16(oc[2], oc[3]);
            }
        }
    }
}

__global__ void __cluster_dims__(4, 1, 1) __launch_bounds__(NTHREADS, 1)
oproj_kernel(const __grid_constant__ CUtensorMap tmO, const __grid_constant__ CUtensorMap tmW0,
             const __grid_constant__ CUtensorMap tmW1, __nv_bfloat16* __restrict__ out) {
    extern __shared__ uint8_t smem_raw[];
    const uint32_t smem_base = (smem_u32(smem_raw) + 1023) & ~1023u;
    const uint32_t full_bar = smem_base + STAGES * STAGE_BYTES;
    const uint32_t empty_bar = full_bar + 8 * STAGES;

    const int idx = blockIdx.x;
    const int blk = idx >> 6;
    const int tile = (idx & 63) >> 2;
    const int mt = tile >> 2, nt = tile & 3;
    const int ks = idx & 3;
    const int warp = threadIdx.x >> 5;

    if (threadIdx.x == 0) {
        for (int s = 0; s < STAGES; ++s) {
            mbar_init(full_bar + 8 * s, 1);
            mbar_init(empty_bar + 8 * s, 2);
        }
        asm volatile("fence.mbarrier_init.release.cluster;" ::: "memory");
    }
    __syncthreads();

    float acc[128];
    if (warp >= 8) {
        if (warp == 8 && (threadIdx.x & 31) == 0) {
            const CUtensorMap* tmW = blk ? &tmW1 : &tmW0;
            for (int it = 0; it < KTILES; ++it) {
                const int s = it % STAGES;
                mbar_wait(empty_bar + 8 * s, ((it / STAGES) & 1) ^ 1);
                const uint32_t st = smem_base + s * STAGE_BYTES;
                mbar_expect_tx(full_bar + 8 * s, STAGE_BYTES);
                tma_load_2d(st, &tmO, full_bar + 8 * s, ks * 1024 + it * BK, blk * 512 + mt * BM);
#pragma unroll
                for (int j = 0; j < 4; ++j)
                    tma_load_2d(st + A_BYTES + j * BOX_BYTES, tmW, full_bar + 8 * s, nt * BN + j * 64,
                                ks * 1024 + it * BK);
            }
        }
        asm volatile("barrier.cluster.arrive.release.aligned;\nbarrier.cluster.wait.acquire.aligned;" ::: "memory");
        asm volatile("barrier.cluster.arrive.release.aligned;\nbarrier.cluster.wait.acquire.aligned;" ::: "memory");
    } else {
        const int wg = warp >> 2;
        const bool leader = (threadIdx.x & 127) == 0;
        mainloop_consumer(acc, smem_base, full_bar, empty_bar, wg, leader);

        asm volatile("barrier.cluster.arrive.release.aligned;\nbarrier.cluster.wait.acquire.aligned;" ::: "memory");
        const int tid = threadIdx.x;
#pragma unroll
        for (int j = 0; j < 4; ++j) {
            if (j != ks) {
                uint32_t dst_local = smem_base + (uint32_t)(ks * 8 * 256 + tid) * 16;
                uint32_t dst;
                asm volatile("mapa.shared::cluster.u32 %0, %1, %2;" : "=r"(dst) : "r"(dst_local), "r"(j));
#pragma unroll
                for (int i = 0; i < 8; ++i) {
                    asm volatile("st.shared::cluster.v4.f32 [%0], {%1, %2, %3, %4};" ::"r"(dst + i * 256 * 16),
                                 "f"(acc[j * 32 + i * 4 + 0]), "f"(acc[j * 32 + i * 4 + 1]),
                                 "f"(acc[j * 32 + i * 4 + 2]), "f"(acc[j * 32 + i * 4 + 3])
                                 : "memory");
                }
            }
        }
        asm volatile("barrier.cluster.arrive.release.aligned;\nbarrier.cluster.wait.acquire.aligned;" ::: "memory");
        const int lane = tid & 31, g = lane >> 2, tq = lane & 3;
        const int row = mt * BM + wg * 64 + (warp & 3) * 16 + g;
        __nv_bfloat16* op = out + (size_t)row * 2048 + blk * 1024 + nt * 256 + ks * 64 + tq * 2;
#pragma unroll
        for (int j = 0; j < 4; ++j) {
            if (j == ks) {
#pragma unroll
                for (int i = 0; i < 8; ++i) {
                    float v0 = acc[j * 32 + i * 4 + 0], v1 = acc[j * 32 + i * 4 + 1];
                    float v2 = acc[j * 32 + i * 4 + 2], v3 = acc[j * 32 + i * 4 + 3];
#pragma unroll
                    for (int sl = 0; sl < 4; ++sl) {
                        if (sl != j) {
                            float4 r;
                            asm volatile("ld.shared.v4.f32 {%0, %1, %2, %3}, [%4];"
                                         : "=f"(r.x), "=f"(r.y), "=f"(r.z), "=f"(r.w)
                                         : "r"(smem_base + (uint32_t)((sl * 8 + i) * 256 + tid) * 16));
                            v0 += r.x; v1 += r.y; v2 += r.z; v3 += r.w;
                        }
                    }
                    *reinterpret_cast<uint32_t*>(op + i * 8) = pack_bf16(v0, v1);
                    *reinterpret_cast<uint32_t*>(op + i * 8 + 8 * 2048) = pack_bf16(v2, v3);
                }
            }
        }
    }
}

typedef CUresult (*EncodeFn)(CUtensorMap*, CUtensorMapDataType, cuuint32_t, void*, const cuuint64_t*,
                             const cuuint64_t*, const cuuint32_t*, const cuuint32_t*, CUtensorMapInterleave,
                             CUtensorMapSwizzle, CUtensorMapL2promotion, CUtensorMapFloatOOBfill);

EncodeFn get_encode() {
    static EncodeFn fn = nullptr;
    if (!fn) {
        void* p = nullptr;
        cudaDriverEntryPointQueryResult qres;
        cudaGetDriverEntryPoint("cuTensorMapEncodeTiled", &p, cudaEnableDefault, &qres);
        fn = (EncodeFn)p;
    }
    return fn;
}

CUtensorMap make_map(const void* ptr, uint64_t inner, uint64_t outer, uint32_t box_inner, uint32_t box_outer) {
    CUtensorMap m;
    cuuint64_t dims[2] = {inner, outer};
    cuuint64_t strides[1] = {inner * 2};
    cuuint32_t box[2] = {box_inner, box_outer};
    cuuint32_t estr[2] = {1, 1};
    get_encode()(&m, CU_TENSOR_MAP_DATA_TYPE_BFLOAT16, 2, const_cast<void*>(ptr), dims, strides, box, estr,
                 CU_TENSOR_MAP_INTERLEAVE_NONE, CU_TENSOR_MAP_SWIZZLE_128B, CU_TENSOR_MAP_L2_PROMOTION_L2_256B,
                 CU_TENSOR_MAP_FLOAT_OOB_FILL_NONE);
    return m;
}

}

extern "C" void kernel_launch(void* const* d_in, const int* in_sizes, int n_in, void* d_out, int out_size) {
    (void)in_sizes; (void)n_in; (void)out_size;
    void* o_scratch = nullptr;
    cudaGetSymbolAddress(&o_scratch, g_o);

    CUtensorMap tmX[2], tmWq[2], tmK[2], tmV[2], tmWo[2];
    for (int b = 0; b < 2; ++b) {
        tmX[b] = make_map(d_in[b * 5 + 0], 1024, 512, 64, 128);
        tmK[b] = make_map(d_in[b * 5 + 1], 128, 16384, 64, 64);
        tmV[b] = make_map(d_in[b * 5 + 2], 128, 16384, 64, 64);
        tmWq[b] = make_map(d_in[b * 5 + 3], 4096, 1024, 64, 64);
        tmWo[b] = make_map(d_in[b * 5 + 4], 1024, 4096, 64, 64);
    }
    CUtensorMap tmO = make_map(o_scratch, 4096, 1024, 64, 128);

    static bool attr_done = false;
    if (!attr_done) {
        cudaFuncSetAttribute(qproj_attn_kernel, cudaFuncAttributeMaxDynamicSharedMemorySize, SMEM_BYTES);
        cudaFuncSetAttribute(oproj_kernel, cudaFuncAttributeMaxDynamicSharedMemorySize, SMEM_BYTES);
        attr_done = true;
    }
    qproj_attn_kernel<<<128, NTHREADS, SMEM_BYTES>>>(tmX[0], tmX[1], tmWq[0], tmWq[1], tmK[0], tmK[1], tmV[0],
                                                     tmV[1]);
    oproj_kernel<<<128, NTHREADS, SMEM_BYTES>>>(tmO, tmWo[0], tmWo[1], (__nv_bfloat16*)d_out);
}
```

```cpp
#include <cuda_runtime.h>
#include <cuda_bf16.h>
#include <cuda.h>
#include <stdint.h>

namespace {

constexpr int BM = 128, BN = 256, BK = 64;
constexpr int STAGES = 4;
constexpr int A_BYTES = BM * BK * 2;
constexpr int B_BYTES = BK * BN * 2;
constexpr int STAGE_BYTES = A_BYTES + B_BYTES;
constexpr int BOX_BYTES = 64 * 64 * 2;
constexpr int NTHREADS = 384;
constexpr int KTILES = 16;
constexpr int SMEM_BYTES = STAGES * STAGE_BYTES + 1024 + 256;

__device__ __nv_bfloat16 g_o[2 * 512 * 4096];

__device__ __forceinline__ uint32_t smem_u32(const void* p) {
    return (uint32_t)__cvta_generic_to_shared(p);
}
__device__ __forceinline__ void mbar_init(uint32_t bar, uint32_t count) {
    asm volatile("mbarrier.init.shared::cta.b64 [%0], %1;" ::"r"(bar), "r"(count));
}
__device__ __forceinline__ void mbar_expect_tx(uint32_t bar, uint32_t bytes) {
    asm volatile("mbarrier.arrive.expect_tx.shared::cta.b64 _, [%0], %1;" ::"r"(bar), "r"(bytes) : "memory");
}
__device__ __forceinline__ void mbar_arrive(uint32_t bar) {
    asm volatile("mbarrier.arrive.shared::cta.b64 _, [%0];" ::"r"(bar) : "memory");
}
__device__ __forceinline__ void mbar_wait(uint32_t bar, uint32_t parity) {
    asm volatile(
        "{\n"
        ".reg .pred P1;\n"
        "LAB_WAIT:\n"
        "mbarrier.try_wait.parity.shared::cta.b64 P1, [%0], %1;\n"
        "@P1 bra DONE;\n"
        "bra LAB_WAIT;\n"
        "DONE:\n"
        "}\n" ::"r"(bar), "r"(parity) : "memory");
}
__device__ __forceinline__ void tma_load_2d(uint32_t dst, const CUtensorMap* tm, uint32_t bar, int c0, int c1) {
    asm volatile(
        "cp.async.bulk.tensor.2d.shared::cluster.global.mbarrier::complete_tx::bytes [%0], [%1, {%3, %4}], [%2];"
        ::"r"(dst), "l"(tm), "r"(bar), "r"(c0), "r"(c1) : "memory");
}
__device__ __forceinline__ void tma_load_2d_mc(uint32_t dst, const CUtensorMap* tm, uint32_t bar, int c0, int c1,
                                               uint16_t mask) {
    asm volatile(
        "cp.async.bulk.tensor.2d.shared::cluster.global.mbarrier::complete_tx::bytes.multicast::cluster "
        "[%0], [%1, {%3, %4}], [%2], %5;"
        ::"r"(dst), "l"(tm), "r"(bar), "r"(c0), "r"(c1), "h"(mask) : "memory");
}
__device__ __forceinline__ void mbar_arrive_cluster(uint32_t bar, uint32_t rank) {
    asm volatile(
        "{\n"
        ".reg .b32 ra;\n"
        "mapa.shared::cluster.u32 ra, %0, %1;\n"
        "mbarrier.arrive.shared::cluster.b64 _, [ra];\n"
        "}\n" ::"r"(bar), "r"(rank) : "memory");
}
__device__ __forceinline__ void cluster_sync_all() {
    asm volatile("barrier.cluster.arrive.release.aligned;\nbarrier.cluster.wait.acquire.aligned;" ::: "memory");
}
__device__ __forceinline__ void wgmma_fence() { asm volatile("wgmma.fence.sync.aligned;" ::: "memory"); }
__device__ __forceinline__ void wgmma_commit() { asm volatile("wgmma.commit_group.sync.aligned;" ::: "memory"); }
template <int N>
__device__ __forceinline__ void wgmma_wait() { asm volatile("wgmma.wait_group.sync.aligned %0;" ::"n"(N) : "memory"); }

__device__ __forceinline__ uint64_t make_desc(uint32_t addr, uint32_t lbo, uint32_t sbo) {
    uint64_t d = 0;
    d |= (uint64_t)((addr & 0x3FFFF) >> 4);
    d |= (uint64_t)((lbo >> 4) & 0x3FFF) << 16;
    d |= (uint64_t)((sbo >> 4) & 0x3FFF) << 32;
    d |= (uint64_t)1 << 62;
    return d;
}

__device__ __forceinline__ void wgmma_m64n256k16(float (&d)[128], uint64_t da, uint64_t db, int scale_d) {
    asm volatile(
        "{\n"
        ".reg .pred p;\n"
        "setp.ne.b32 p, %130, 0;\n"
        "wgmma.mma_async.sync.aligned.m64n256k16.f32.bf16.bf16 "
        "{%0, %1, %2, %3, %4, %5, %6, %7, %8, %9, %10, %11, %12, %13, %14, %15, "
        "%16, %17, %18, %19, %20, %21, %22, %23, %24, %25, %26, %27, %28, %29, %30, %31, "
        "%32, %33, %34, %35, %36, %37, %38, %39, %40, %41, %42, %43, %44, %45, %46, %47, "
        "%48, %49, %50, %51, %52, %53, %54, %55, %56, %57, %58, %59, %60, %61, %62, %63, "
        "%64, %65, %66, %67, %68, %69, %70, %71, %72, %73, %74, %75, %76, %77, %78, %79, "
        "%80, %81, %82, %83, %84, %85, %86, %87, %88, %89, %90, %91, %92, %93, %94, %95, "
        "%96, %97, %98, %99, %100, %101, %102, %103, %104, %105, %106, %107, %108, %109, %110, %111, "
        "%112, %113, %114, %115, %116, %117, %118, %119, %120, %121, %122, %123, %124, %125, %126, %127}, "
        "%128, %129, p, 1, 1, 0, 1;\n"
        "}\n"
        : "+f"(d[0]), "+f"(d[1]), "+f"(d[2]), "+f"(d[3]), "+f"(d[4]), "+f"(d[5]), "+f"(d[6]), "+f"(d[7]),
          "+f"(d[8]), "+f"(d[9]), "+f"(d[10]), "+f"(d[11]), "+f"(d[12]), "+f"(d[13]), "+f"(d[14]), "+f"(d[15]),
          "+f"(d[16]), "+f"(d[17]), "+f"(d[18]), "+f"(d[19]), "+f"(d[20]), "+f"(d[21]), "+f"(d[22]), "+f"(d[23]),
          "+f"(d[24]), "+f"(d[25]), "+f"(d[26]), "+f"(d[27]), "+f"(d[28]), "+f"(d[29]), "+f"(d[30]), "+f"(d[31]),
          "+f"(d[32]), "+f"(d[33]), "+f"(d[34]), "+f"(d[35]), "+f"(d[36]), "+f"(d[37]), "+f"(d[38]), "+f"(d[39]),
          "+f"(d[40]), "+f"(d[41]), "+f"(d[42]), "+f"(d[43]), "+f"(d[44]), "+f"(d[45]), "+f"(d[46]), "+f"(d[47]),
          "+f"(d[48]), "+f"(d[49]), "+f"(d[50]), "+f"(d[51]), "+f"(d[52]), "+f"(d[53]), "+f"(d[54]), "+f"(d[55]),
          "+f"(d[56]), "+f"(d[57]), "+f"(d[58]), "+f"(d[59]), "+f"(d[60]), "+f"(d[61]), "+f"(d[62]), "+f"(d[63]),
          "+f"(d[64]), "+f"(d[65]), "+f"(d[66]), "+f"(d[67]), "+f"(d[68]), "+f"(d[69]), "+f"(d[70]), "+f"(d[71]),
          "+f"(d[72]), "+f"(d[73]), "+f"(d[74]), "+f"(d[75]), "+f"(d[76]), "+f"(d[77]), "+f"(d[78]), "+f"(d[79]),
          "+f"(d[80]), "+f"(d[81]), "+f"(d[82]), "+f"(d[83]), "+f"(d[84]), "+f"(d[85]), "+f"(d[86]), "+f"(d[87]),
          "+f"(d[88]), "+f"(d[89]), "+f"(d[90]), "+f"(d[91]), "+f"(d[92]), "+f"(d[93]), "+f"(d[94]), "+f"(d[95]),
          "+f"(d[96]), "+f"(d[97]), "+f"(d[98]), "+f"(d[99]), "+f"(d[100]), "+f"(d[101]), "+f"(d[102]), "+f"(d[103]),
          "+f"(d[104]), "+f"(d[105]), "+f"(d[106]), "+f"(d[107]), "+f"(d[108]), "+f"(d[109]), "+f"(d[110]), "+f"(d[111]),
          "+f"(d[112]), "+f"(d[113]), "+f"(d[114]), "+f"(d[115]), "+f"(d[116]), "+f"(d[117]), "+f"(d[118]), "+f"(d[119]),
          "+f"(d[120]), "+f"(d[121]), "+f"(d[122]), "+f"(d[123]), "+f"(d[124]), "+f"(d[125]), "+f"(d[126]), "+f"(d[127])
        : "l"(da), "l"(db), "r"(scale_d));
}

__device__ __forceinline__ void ldsm_x4(uint32_t addr, uint32_t& r0, uint32_t& r1, uint32_t& r2, uint32_t& r3) {
    asm volatile("ldmatrix.sync.aligned.m8n8.x4.shared.b16 {%0, %1, %2, %3}, [%4];"
                 : "=r"(r0), "=r"(r1), "=r"(r2), "=r"(r3) : "r"(addr));
}
__device__ __forceinline__ void ldsm_x4_t(uint32_t addr, uint32_t& r0, uint32_t& r1, uint32_t& r2, uint32_t& r3) {
    asm volatile("ldmatrix.sync.aligned.m8n8.x4.trans.shared.b16 {%0, %1, %2, %3}, [%4];"
                 : "=r"(r0), "=r"(r1), "=r"(r2), "=r"(r3) : "r"(addr));
}
__device__ __forceinline__ void mma_bf16(float (&c)[4], uint32_t a0, uint32_t a1, uint32_t a2, uint32_t a3,
                                         uint32_t b0, uint32_t b1) {
    asm volatile(
        "mma.sync.aligned.m16n8k16.row.col.f32.bf16.bf16.f32 {%0, %1, %2, %3}, {%4, %5, %6, %7}, {%8, %9}, "
        "{%0, %1, %2, %3};"
        : "+f"(c[0]), "+f"(c[1]), "+f"(c[2]), "+f"(c[3])
        : "r"(a0), "r"(a1), "r"(a2), "r"(a3), "r"(b0), "r"(b1));
}
__device__ __forceinline__ uint32_t pack_bf16(float lo, float hi) {
    __nv_bfloat162 v = __floats2bfloat162_rn(lo, hi);
    return *reinterpret_cast<uint32_t*>(&v);
}
__device__ __forceinline__ float bf16_round(float x) { return __bfloat162float(__float2bfloat16_rn(x)); }

__device__ __forceinline__ void mainloop_consumer(float (&acc)[128], uint32_t smem_base, uint32_t full_bar,
                                                  uint32_t empty_bar, int wg, bool leader) {
#pragma unroll 1
    for (int it = 0; it < KTILES; ++it) {
        const int s = it % STAGES;
        mbar_wait(full_bar + 8 * s, (it / STAGES) & 1);
        const uint32_t a_addr = smem_base + s * STAGE_BYTES + wg * (64 * 128);
        const uint32_t b_addr = smem_base + s * STAGE_BYTES + A_BYTES;
        wgmma_fence();
#pragma unroll
        for (int k = 0; k < 4; ++k) {
            uint64_t da = make_desc(a_addr + k * 32, 16, 1024);
            uint64_t db = make_desc(b_addr + k * 2048, BOX_BYTES, 1024);
            wgmma_m64n256k16(acc, da, db, (it | k) != 0);
        }
        wgmma_commit();
        if (it > 0) {
            wgmma_wait<1>();
            if (leader) {
                mbar_arrive_cluster(empty_bar + 8 * ((it - 1) % STAGES), 0);
                mbar_arrive_cluster(empty_bar + 8 * ((it - 1) % STAGES), 1);
            }
        }
    }
    wgmma_wait<0>();
    if (leader) {
        mbar_arrive_cluster(empty_bar + 8 * ((KTILES - 1) % STAGES), 0);
        mbar_arrive_cluster(empty_bar + 8 * ((KTILES - 1) % STAGES), 1);
    }
}

__global__ void __cluster_dims__(2, 1, 1) __launch_bounds__(NTHREADS, 1)
qproj_attn_kernel(const __grid_constant__ CUtensorMap tmX0, const __grid_constant__ CUtensorMap tmX1,
                  const __grid_constant__ CUtensorMap tmW0, const __grid_constant__ CUtensorMap tmW1,
                  const __grid_constant__ CUtensorMap tmK0, const __grid_constant__ CUtensorMap tmK1,
                  const __grid_constant__ CUtensorMap tmV0, const __grid_constant__ CUtensorMap tmV1) {
    extern __shared__ uint8_t smem_raw[];
    const uint32_t smem_base = (smem_u32(smem_raw) + 1023) & ~1023u;
    const uint32_t full_bar = smem_base + STAGES * STAGE_BYTES;
    const uint32_t empty_bar = full_bar + 8 * STAGES;

    const int idx = blockIdx.x;
    const int blk = idx >> 6;
    const int nt = (idx & 63) >> 2;
    const int mt = idx & 3;
    const uint32_t crank = idx & 1;
    const int warp = threadIdx.x >> 5;
    const int lane = threadIdx.x & 31;

    if (threadIdx.x == 0) {
        for (int s = 0; s < STAGES; ++s) {
            mbar_init(full_bar + 8 * s, 1);
            mbar_init(empty_bar + 8 * s, 4);
        }
        asm volatile("fence.mbarrier_init.release.cluster;" ::: "memory");
    }
    __syncthreads();
    cluster_sync_all();

    if (warp >= 8) {
        if (warp == 8 && lane == 0) {
            const CUtensorMap* tmX = blk ? &tmX1 : &tmX0;
            const CUtensorMap* tmW = blk ? &tmW1 : &tmW0;
            const CUtensorMap* tmK = blk ? &tmK1 : &tmK0;
            const CUtensorMap* tmV = blk ? &tmV1 : &tmV0;
            for (int it = 0; it < KTILES; ++it) {
                const int s = it % STAGES;
                mbar_wait(empty_bar + 8 * s, ((it / STAGES) & 1) ^ 1);
                const uint32_t st = smem_base + s * STAGE_BYTES;
                mbar_expect_tx(full_bar + 8 * s, STAGE_BYTES);
                tma_load_2d(st, tmX, full_bar + 8 * s, it * BK, mt * BM);
#pragma unroll
                for (int jj = 0; jj < 2; ++jj) {
                    const int j = crank * 2 + jj;
                    tma_load_2d_mc(st + A_BYTES + j * BOX_BYTES, tmW, full_bar + 8 * s, nt * BN + j * 64, it * BK,
                                   (uint16_t)3);
                }
            }
            for (int t = 0; t < 3; ++t) {
                const int it = KTILES + t;
                const int s = it % STAGES;
                mbar_wait(empty_bar + 8 * s, ((it / STAGES) & 1) ^ 1);
                const int nbox = (t < 2) ? 6 : 4;
                mbar_expect_tx(full_bar + 8 * s, nbox * BOX_BYTES);
                for (int j = 0; j < nbox; ++j) {
                    const int e = t * 6 + j;
                    const int kv = e >> 3, bl = (e >> 1) & 3, half = e & 1;
                    const int row0 = ((mt * 4 + bl) * 32 + nt * 2) * 32;
                    tma_load_2d(smem_base + s * STAGE_BYTES + j * BOX_BYTES, kv ? tmV : tmK, full_bar + 8 * s,
                                half * 64, row0);
                }
            }
        }
    } else {
        const int wg = warp >> 2;
        const bool leader = (threadIdx.x & 127) == 0;
        float acc[128];
        mainloop_consumer(acc, smem_base, full_bar, empty_bar, wg, leader);

        uint32_t qf[64];
#pragma unroll
        for (int i = 0; i < 64; ++i) qf[i] = pack_bf16(acc[2 * i], acc[2 * i + 1]);

#pragma unroll
        for (int t = 0; t < 3; ++t) {
            const int it = KTILES + t;
            mbar_wait(full_bar + 8 * (it % STAGES), (it / STAGES) & 1);
        }
        const int bl = wg * 2 + ((warp & 3) >> 1);
        const uint32_t kbase = smem_base + (bl * 2) * BOX_BYTES;
        const uint32_t vbase = smem_base + (8 + bl * 2) * BOX_BYTES;
        const int g = lane >> 2, tq = lane & 3;
        const int row_g = mt * BM + wg * 64 + (warp & 3) * 16 + g;
        __nv_bfloat16* o_ptr = g_o + ((size_t)blk * 512 + row_g) * 4096 + (size_t)nt * 256;

#pragma unroll
        for (int hh = 0; hh < 2; ++hh) {
            float sc[4][4];
#pragma unroll
            for (int n = 0; n < 4; ++n)
#pragma unroll
                for (int c = 0; c < 4; ++c) sc[n][c] = 0.f;
#pragma unroll
            for (int kk = 0; kk < 8; kk += 2) {
                const int chunk = 2 * kk + (lane >> 3);
                const int half = chunk >> 3, c8 = chunk & 7;
#pragma unroll
                for (int n = 0; n < 4; ++n) {
                    const int r = hh * 32 + n * 8 + (lane & 7);
                    const uint32_t addr = kbase + half * BOX_BYTES + r * 128 + ((c8 ^ (r & 7)) << 4);
                    uint32_t b0, b1, b2, b3;
                    ldsm_x4(addr, b0, b1, b2, b3);
                    const int q0 = hh * 32 + kk * 4;
                    mma_bf16(sc[n], qf[q0 + 0], qf[q0 + 1], qf[q0 + 2], qf[q0 + 3], b0, b1);
                    mma_bf16(sc[n], qf[q0 + 4], qf[q0 + 5], qf[q0 + 6], qf[q0 + 7], b2, b3);
                }
            }
            const float scale = 0.08838834764831845f;
            float m0 = -INFINITY, m1 = -INFINITY;
#pragma unroll
            for (int n = 0; n < 4; ++n) {
#pragma unroll
                for (int c = 0; c < 4; ++c) sc[n][c] = bf16_round(bf16_round(sc[n][c]) * scale);
                m0 = fmaxf(m0, fmaxf(sc[n][0], sc[n][1]));
                m1 = fmaxf(m1, fmaxf(sc[n][2], sc[n][3]));
            }
            m0 = fmaxf(m0, __shfl_xor_sync(0xffffffffu, m0, 1));
            m0 = fmaxf(m0, __shfl_xor_sync(0xffffffffu, m0, 2));
            m1 = fmaxf(m1, __shfl_xor_sync(0xffffffffu, m1, 1));
            m1 = fmaxf(m1, __shfl_xor_sync(0xffffffffu, m1, 2));
            float s0 = 0.f, s1 = 0.f;
#pragma unroll
            for (int n = 0; n < 4; ++n) {
                sc[n][0] = __expf(sc[n][0] - m0);
                sc[n][1] = __expf(sc[n][1] - m0);
                sc[n][2] = __expf(sc[n][2] - m1);
                sc[n][3] = __expf(sc[n][3] - m1);
                s0 += sc[n][0] + sc[n][1];
                s1 += sc[n][2] + sc[n][3];
            }
            s0 += __shfl_xor_sync(0xffffffffu, s0, 1);
            s0 += __shfl_xor_sync(0xffffffffu, s0, 2);
            s1 += __shfl_xor_sync(0xffffffffu, s1, 1);
            s1 += __shfl_xor_sync(0xffffffffu, s1, 2);
            const float i0 = 1.f / s0, i1 = 1.f / s1;
            uint32_t pf[2][4];
#pragma unroll
            for (int kk = 0; kk < 2; ++kk) {
                pf[kk][0] = pack_bf16(sc[2 * kk][0] * i0, sc[2 * kk][1] * i0);
                pf[kk][1] = pack_bf16(sc[2 * kk][2] * i1, sc[2 * kk][3] * i1);
                pf[kk][2] = pack_bf16(sc[2 * kk + 1][0] * i0, sc[2 * kk + 1][1] * i0);
                pf[kk][3] = pack_bf16(sc[2 * kk + 1][2] * i1, sc[2 * kk + 1][3] * i1);
            }
#pragma unroll
            for (int n = 0; n < 16; ++n) {
                const int r = hh * 32 + lane;
                const int half = n >> 3, c8 = n & 7;
                const uint32_t addr = vbase + half * BOX_BYTES + r * 128 + ((c8 ^ (r & 7)) << 4);
                uint32_t b0, b1, b2, b3;
                ldsm_x4_t(addr, b0, b1, b2, b3);
                float oc[4] = {0.f, 0.f, 0.f, 0.f};
                mma_bf16(oc, pf[0][0], pf[0][1], pf[0][2], pf[0][3], b0, b1);
                mma_bf16(oc, pf[1][0], pf[1][1], pf[1][2], pf[1][3], b2, b3);
                __nv_bfloat16* p = o_ptr + hh * 128 + n * 8 + tq * 2;
                *reinterpret_cast<uint32_t*>(p) = pack_bf16(oc[0], oc[1]);
                *reinterpret_cast<uint32_t*>(p + 8 * 4096) = pack_bf16(oc[2], oc[3]);
            }
        }
    }
    cluster_sync_all();
}

__device__ float4 g_red[32 * 4 * 4 * 8 * 256];
__device__ unsigned int g_flag[32 * 4 * 2];

__global__ void __cluster_dims__(2, 1, 1) __launch_bounds__(NTHREADS, 1)
oproj_kernel(const __grid_constant__ CUtensorMap tmO, const __grid_constant__ CUtensorMap tmW0,
             const __grid_constant__ CUtensorMap tmW1, __nv_bfloat16* __restrict__ out) {
    extern __shared__ uint8_t smem_raw[];
    const uint32_t smem_base = (smem_u32(smem_raw) + 1023) & ~1023u;
    const uint32_t full_bar = smem_base + STAGES * STAGE_BYTES;
    const uint32_t empty_bar = full_bar + 8 * STAGES;

    const int idx = blockIdx.x;
    const int blk = idx >> 6;
    const int ks = (idx >> 4) & 3;
    const int nt = (idx >> 2) & 3;
    const int mt = idx & 3;
    const uint32_t crank = idx & 1;
    const int tile = blk * 16 + mt * 4 + nt;
    const int warp = threadIdx.x >> 5;

    if (threadIdx.x == 0) {
        for (int s = 0; s < STAGES; ++s) {
            mbar_init(full_bar + 8 * s, 1);
            mbar_init(empty_bar + 8 * s, 4);
        }
        asm volatile("fence.mbarrier_init.release.cluster;" ::: "memory");
    }
    __syncthreads();
    cluster_sync_all();

    if (warp >= 8) {
        if (warp == 8 && (threadIdx.x & 31) == 0) {
            const CUtensorMap* tmW = blk ? &tmW1 : &tmW0;
            for (int it = 0; it < KTILES; ++it) {
                const int s = it % STAGES;
                mbar_wait(empty_bar + 8 * s, ((it / STAGES) & 1) ^ 1);
                const uint32_t st = smem_base + s * STAGE_BYTES;
                mbar_expect_tx(full_bar + 8 * s, STAGE_BYTES);
                tma_load_2d(st, &tmO, full_bar + 8 * s, ks * 1024 + it * BK, blk * 512 + mt * BM);
#pragma unroll
                for (int jj = 0; jj < 2; ++jj) {
                    const int j = crank * 2 + jj;
                    tma_load_2d_mc(st + A_BYTES + j * BOX_BYTES, tmW, full_bar + 8 * s, nt * BN + j * 64,
                                   ks * 1024 + it * BK, (uint16_t)3);
                }
            }
        }
    } else {
        const int wg = warp >> 2;
        const bool leader = (threadIdx.x & 127) == 0;
        float acc[128];
        mainloop_consumer(acc, smem_base, full_bar, empty_bar, wg, leader);

        const int tid = threadIdx.x;
#pragma unroll
        for (int j = 0; j < 4; ++j) {
            if (j != ks) {
                float4* dst = g_red + ((size_t)((tile * 4 + j) * 4 + ks) * 8) * 256 + tid;
#pragma unroll
                for (int i = 0; i < 8; ++i)
                    __stcg(dst + i * 256, make_float4(acc[j * 32 + i * 4 + 0], acc[j * 32 + i * 4 + 1],
                                                      acc[j * 32 + i * 4 + 2], acc[j * 32 + i * 4 + 3]));
            }
        }
        __threadfence();
        asm volatile("bar.sync %0, 128;" ::"r"(1 + wg) : "memory");
        if (leader) {
#pragma unroll
            for (int j = 0; j < 4; ++j)
                if (j != ks) atomicAdd(&g_flag[(tile * 4 + j) * 2 + wg], 1u);
            volatile unsigned int* f = &g_flag[(tile * 4 + ks) * 2 + wg];
            unsigned int spins = 0;
            while (*f < 3u && ++spins < (1u << 26)) { }
            *f = 0;
            __threadfence();
        }
        asm volatile("bar.sync %0, 128;" ::"r"(1 + wg) : "memory");
        const int lane = tid & 31, g = lane >> 2, tq = lane & 3;
        const int row = mt * BM + wg * 64 + (warp & 3) * 16 + g;
        __nv_bfloat16* op = out + (size_t)row * 2048 + blk * 1024 + nt * 256 + ks * 64 + tq * 2;
#pragma unroll
        for (int j = 0; j < 4; ++j) {
            if (j == ks) {
#pragma unroll
                for (int i = 0; i < 8; ++i) {
                    float v0 = acc[j * 32 + i * 4 + 0], v1 = acc[j * 32 + i * 4 + 1];
                    float v2 = acc[j * 32 + i * 4 + 2], v3 = acc[j * 32 + i * 4 + 3];
#pragma unroll
                    for (int sl = 0; sl < 4; ++sl) {
                        if (sl != j) {
                            float4 r = __ldcg(g_red + ((size_t)((tile * 4 + j) * 4 + sl) * 8 + i) * 256 + tid);
                            v0 += r.x; v1 += r.y; v2 += r.z; v3 += r.w;
                        }
                    }
                    *reinterpret_cast<uint32_t*>(op + i * 8) = pack_bf16(v0, v1);
                    *reinterpret_cast<uint32_t*>(op + i * 8 + 8 * 2048) = pack_bf16(v2, v3);
                }
            }
        }
    }
    cluster_sync_all();
}

typedef CUresult (*EncodeFn)(CUtensorMap*, CUtensorMapDataType, cuuint32_t, void*, const cuuint64_t*,
                             const cuuint64_t*, const cuuint32_t*, const cuuint32_t*, CUtensorMapInterleave,
                             CUtensorMapSwizzle, CUtensorMapL2promotion, CUtensorMapFloatOOBfill);

EncodeFn get_encode() {
    static EncodeFn fn = nullptr;
    if (!fn) {
        void* p = nullptr;
        cudaDriverEntryPointQueryResult qres;
        cudaGetDriverEntryPoint("cuTensorMapEncodeTiled", &p, cudaEnableDefault, &qres);
        fn = (EncodeFn)p;
    }
    return fn;
}

CUtensorMap make_map(const void* ptr, uint64_t inner, uint64_t outer, uint32_t box_inner, uint32_t box_outer) {
    CUtensorMap m;
    cuuint64_t dims[2] = {inner, outer};
    cuuint64_t strides[1] = {inner * 2};
    cuuint32_t box[2] = {box_inner, box_outer};
    cuuint32_t estr[2] = {1, 1};
    get_encode()(&m, CU_TENSOR_MAP_DATA_TYPE_BFLOAT16, 2, const_cast<void*>(ptr), dims, strides, box, estr,
                 CU_TENSOR_MAP_INTERLEAVE_NONE, CU_TENSOR_MAP_SWIZZLE_128B, CU_TENSOR_MAP_L2_PROMOTION_L2_256B,
                 CU_TENSOR_MAP_FLOAT_OOB_FILL_NONE);
    return m;
}

}

extern "C" void kernel_launch(void* const* d_in, const int* in_sizes, int n_in, void* d_out, int out_size) {
    (void)in_sizes; (void)n_in; (void)out_size;
    void* o_scratch = nullptr;
    cudaGetSymbolAddress(&o_scratch, g_o);

    CUtensorMap tmX[2], tmWq[2], tmK[2], tmV[2], tmWo[2];
    for (int b = 0; b < 2; ++b) {
        tmX[b] = make_map(d_in[b * 5 + 0], 1024, 512, 64, 128);
        tmK[b] = make_map(d_in[b * 5 + 1], 128, 16384, 64, 64);
        tmV[b] = make_map(d_in[b * 5 + 2], 128, 16384, 64, 64);
        tmWq[b] = make_map(d_in[b * 5 + 3], 4096, 1024, 64, 64);
        tmWo[b] = make_map(d_in[b * 5 + 4], 1024, 4096, 64, 64);
    }
    CUtensorMap tmO = make_map(o_scratch, 4096, 1024, 64, 128);

    static bool attr_done = false;
    if (!attr_done) {
        cudaFuncSetAttribute(qproj_attn_kernel, cudaFuncAttributeMaxDynamicSharedMemorySize, SMEM_BYTES);
        cudaFuncSetAttribute(oproj_kernel, cudaFuncAttributeMaxDynamicSharedMemorySize, SMEM_BYTES);
        attr_done = true;
    }
    qproj_attn_kernel<<<128, NTHREADS, SMEM_BYTES>>>(tmX[0], tmX[1], tmWq[0], tmWq[1], tmK[0], tmK[1], tmV[0],
                                                     tmV[1]);
    oproj_kernel<<<128, NTHREADS, SMEM_BYTES>>>(tmO, tmWo[0], tmWo[1], (__nv_bfloat16*)d_out);
}
```

```cpp
#include <cuda_runtime.h>
#include <cuda_bf16.h>
#include <cuda.h>
#include <stdint.h>

namespace {

constexpr int BM = 128, BN = 256;
constexpr int STAGES = 4;
constexpr int BOX_BYTES = 64 * 64 * 2;
constexpr int NTHREADS = 384;
constexpr int K1_BK = 32;
constexpr int K1_STAGE = (BM + BN) * K1_BK * 2;
constexpr int K1_KV_OFF = STAGES * K1_STAGE;
constexpr int K1_BAR_OFF = K1_KV_OFF + 16 * BOX_BYTES;
constexpr int K1_SMEM = K1_BAR_OFF + 128 + 1024;
constexpr int K2_BK = 64;
constexpr int K2_STAGE = (BM + BN) * K2_BK * 2;
constexpr int K2_BAR_OFF = STAGES * K2_STAGE;
constexpr int K2_SMEM = K2_BAR_OFF + 128 + 1024;

__device__ __nv_bfloat16 g_o[2 * 512 * 4096];

#define STAMP(k, i) do { } while (0)

__device__ __forceinline__ uint32_t smem_u32(const void* p) {
    return (uint32_t)__cvta_generic_to_shared(p);
}
__device__ __forceinline__ void mbar_init(uint32_t bar, uint32_t count) {
    asm volatile("mbarrier.init.shared::cta.b64 [%0], %1;" ::"r"(bar), "r"(count));
}
__device__ __forceinline__ void mbar_expect_tx(uint32_t bar, uint32_t bytes) {
    asm volatile("mbarrier.arrive.expect_tx.shared::cta.b64 _, [%0], %1;" ::"r"(bar), "r"(bytes) : "memory");
}
__device__ __forceinline__ void mbar_arrive(uint32_t bar) {
    asm volatile("mbarrier.arrive.shared::cta.b64 _, [%0];" ::"r"(bar) : "memory");
}
__device__ __forceinline__ void mbar_wait(uint32_t bar, uint32_t parity) {
    asm volatile(
        "{\n"
        ".reg .pred P1;\n"
        "LAB_WAIT:\n"
        "mbarrier.try_wait.parity.shared::cta.b64 P1, [%0], %1;\n"
        "@P1 bra DONE;\n"
        "bra LAB_WAIT;\n"
        "DONE:\n"
        "}\n" ::"r"(bar), "r"(parity) : "memory");
}
__device__ __forceinline__ void tma_load_2d(uint32_t dst, const CUtensorMap* tm, uint32_t bar, int c0, int c1) {
    asm volatile(
        "cp.async.bulk.tensor.2d.shared::cluster.global.mbarrier::complete_tx::bytes [%0], [%1, {%3, %4}], [%2];"
        ::"r"(dst), "l"(tm), "r"(bar), "r"(c0), "r"(c1) : "memory");
}
__device__ __forceinline__ void tma_load_2d_mc(uint32_t dst, const CUtensorMap* tm, uint32_t bar, int c0, int c1,
                                               uint16_t mask) {
    asm volatile(
        "cp.async.bulk.tensor.2d.shared::cluster.global.mbarrier::complete_tx::bytes.multicast::cluster "
        "[%0], [%1, {%3, %4}], [%2], %5;"
        ::"r"(dst), "l"(tm), "r"(bar), "r"(c0), "r"(c1), "h"(mask) : "memory");
}
__device__ __forceinline__ void mbar_arrive_cluster(uint32_t bar, uint32_t rank) {
    asm volatile(
        "{\n"
        ".reg .b32 ra;\n"
        "mapa.shared::cluster.u32 ra, %0, %1;\n"
        "mbarrier.arrive.shared::cluster.b64 _, [ra];\n"
        "}\n" ::"r"(bar), "r"(rank) : "memory");
}
__device__ __forceinline__ void cluster_sync_all() {
    asm volatile("barrier.cluster.arrive.release.aligned;\nbarrier.cluster.wait.acquire.aligned;" ::: "memory");
}
__device__ __forceinline__ void tma_store_2d(const CUtensorMap* tm, uint32_t src, int c0, int c1) {
    asm volatile("cp.async.bulk.tensor.2d.global.shared::cta.bulk_group [%0, {%2, %3}], [%1];"
                 ::"l"(tm), "r"(src), "r"(c0), "r"(c1) : "memory");
}
__device__ __forceinline__ void tma_store_commit_wait() {
    asm volatile("cp.async.bulk.commit_group;\ncp.async.bulk.wait_group 0;" ::: "memory");
}
__device__ __forceinline__ void fence_async_smem() { asm volatile("fence.proxy.async.shared::cta;" ::: "memory"); }
__device__ __forceinline__ void stsm_x4(uint32_t addr, uint32_t r0, uint32_t r1, uint32_t r2, uint32_t r3) {
    asm volatile("stmatrix.sync.aligned.m8n8.x4.shared.b16 [%0], {%1, %2, %3, %4};"
                 ::"r"(addr), "r"(r0), "r"(r1), "r"(r2), "r"(r3) : "memory");
}
__device__ __forceinline__ void wg_bar(int wg) { asm volatile("bar.sync %0, 128;" ::"r"(1 + wg) : "memory"); }
__device__ __forceinline__ void wgmma_fence() { asm volatile("wgmma.fence.sync.aligned;" ::: "memory"); }
__device__ __forceinline__ void wgmma_commit() { asm volatile("wgmma.commit_group.sync.aligned;" ::: "memory"); }
template <int N>
__device__ __forceinline__ void wgmma_wait() { asm volatile("wgmma.wait_group.sync.aligned %0;" ::"n"(N) : "memory"); }

__device__ __forceinline__ uint64_t make_desc(uint32_t addr, uint32_t lbo, uint32_t sbo, uint32_t swz = 1) {
    uint64_t d = 0;
    d |= (uint64_t)((addr & 0x3FFFF) >> 4);
    d |= (uint64_t)((lbo >> 4) & 0x3FFF) << 16;
    d |= (uint64_t)((sbo >> 4) & 0x3FFF) << 32;
    d |= (uint64_t)swz << 62;
    return d;
}

__device__ __forceinline__ void wgmma_m64n256k16(float (&d)[128], uint64_t da, uint64_t db, int scale_d) {
    asm volatile(
        "{\n"
        ".reg .pred p;\n"
        "setp.ne.b32 p, %130, 0;\n"
        "wgmma.mma_async.sync.aligned.m64n256k16.f32.bf16.bf16 "
        "{%0, %1, %2, %3, %4, %5, %6, %7, %8, %9, %10, %11, %12, %13, %14, %15, "
        "%16, %17, %18, %19, %20, %21, %22, %23, %24, %25, %26, %27, %28, %29, %30, %31, "
        "%32, %33, %34, %35, %36, %37, %38, %39, %40, %41, %42, %43, %44, %45, %46, %47, "
        "%48, %49, %50, %51, %52, %53, %54, %55, %56, %57, %58, %59, %60, %61, %62, %63, "
        "%64, %65, %66, %67, %68, %69, %70, %71, %72, %73, %74, %75, %76, %77, %78, %79, "
        "%80, %81, %82, %83, %84, %85, %86, %87, %88, %89, %90, %91, %92, %93, %94, %95, "
        "%96, %97, %98, %99, %100, %101, %102, %103, %104, %105, %106, %107, %108, %109, %110, %111, "
        "%112, %113, %114, %115, %116, %117, %118, %119, %120, %121, %122, %123, %124, %125, %126, %127}, "
        "%128, %129, p, 1, 1, 0, 1;\n"
        "}\n"
        : "+f"(d[0]), "+f"(d[1]), "+f"(d[2]), "+f"(d[3]), "+f"(d[4]), "+f"(d[5]), "+f"(d[6]), "+f"(d[7]),
          "+f"(d[8]), "+f"(d[9]), "+f"(d[10]), "+f"(d[11]), "+f"(d[12]), "+f"(d[13]), "+f"(d[14]), "+f"(d[15]),
          "+f"(d[16]), "+f"(d[17]), "+f"(d[18]), "+f"(d[19]), "+f"(d[20]), "+f"(d[21]), "+f"(d[22]), "+f"(d[23]),
          "+f"(d[24]), "+f"(d[25]), "+f"(d[26]), "+f"(d[27]), "+f"(d[28]), "+f"(d[29]), "+f"(d[30]), "+f"(d[31]),
          "+f"(d[32]), "+f"(d[33]), "+f"(d[34]), "+f"(d[35]), "+f"(d[36]), "+f"(d[37]), "+f"(d[38]), "+f"(d[39]),
          "+f"(d[40]), "+f"(d[41]), "+f"(d[42]), "+f"(d[43]), "+f"(d[44]), "+f"(d[45]), "+f"(d[46]), "+f"(d[47]),
          "+f"(d[48]), "+f"(d[49]), "+f"(d[50]), "+f"(d[51]), "+f"(d[52]), "+f"(d[53]), "+f"(d[54]), "+f"(d[55]),
          "+f"(d[56]), "+f"(d[57]), "+f"(d[58]), "+f"(d[59]), "+f"(d[60]), "+f"(d[61]), "+f"(d[62]), "+f"(d[63]),
          "+f"(d[64]), "+f"(d[65]), "+f"(d[66]), "+f"(d[67]), "+f"(d[68]), "+f"(d[69]), "+f"(d[70]), "+f"(d[71]),
          "+f"(d[72]), "+f"(d[73]), "+f"(d[74]), "+f"(d[75]), "+f"(d[76]), "+f"(d[77]), "+f"(d[78]), "+f"(d[79]),
          "+f"(d[80]), "+f"(d[81]), "+f"(d[82]), "+f"(d[83]), "+f"(d[84]), "+f"(d[85]), "+f"(d[86]), "+f"(d[87]),
          "+f"(d[88]), "+f"(d[89]), "+f"(d[90]), "+f"(d[91]), "+f"(d[92]), "+f"(d[93]), "+f"(d[94]), "+f"(d[95]),
          "+f"(d[96]), "+f"(d[97]), "+f"(d[98]), "+f"(d[99]), "+f"(d[100]), "+f"(d[101]), "+f"(d[102]), "+f"(d[103]),
          "+f"(d[104]), "+f"(d[105]), "+f"(d[106]), "+f"(d[107]), "+f"(d[108]), "+f"(d[109]), "+f"(d[110]), "+f"(d[111]),
          "+f"(d[112]), "+f"(d[113]), "+f"(d[114]), "+f"(d[115]), "+f"(d[116]), "+f"(d[117]), "+f"(d[118]), "+f"(d[119]),
          "+f"(d[120]), "+f"(d[121]), "+f"(d[122]), "+f"(d[123]), "+f"(d[124]), "+f"(d[125]), "+f"(d[126]), "+f"(d[127])
        : "l"(da), "l"(db), "r"(scale_d));
}

__device__ __forceinline__ void ldsm_x4(uint32_t addr, uint32_t& r0, uint32_t& r1, uint32_t& r2, uint32_t& r3) {
    asm volatile("ldmatrix.sync.aligned.m8n8.x4.shared.b16 {%0, %1, %2, %3}, [%4];"
                 : "=r"(r0), "=r"(r1), "=r"(r2), "=r"(r3) : "r"(addr));
}
__device__ __forceinline__ void ldsm_x4_t(uint32_t addr, uint32_t& r0, uint32_t& r1, uint32_t& r2, uint32_t& r3) {
    asm volatile("ldmatrix.sync.aligned.m8n8.x4.trans.shared.b16 {%0, %1, %2, %3}, [%4];"
                 : "=r"(r0), "=r"(r1), "=r"(r2), "=r"(r3) : "r"(addr));
}
__device__ __forceinline__ void mma_bf16(float (&c)[4], uint32_t a0, uint32_t a1, uint32_t a2, uint32_t a3,
                                         uint32_t b0, uint32_t b1) {
    asm volatile(
        "mma.sync.aligned.m16n8k16.row.col.f32.bf16.bf16.f32 {%0, %1, %2, %3}, {%4, %5, %6, %7}, {%8, %9}, "
        "{%0, %1, %2, %3};"
        : "+f"(c[0]), "+f"(c[1]), "+f"(c[2]), "+f"(c[3])
        : "r"(a0), "r"(a1), "r"(a2), "r"(a3), "r"(b0), "r"(b1));
}
__device__ __forceinline__ uint32_t pack_bf16(float lo, float hi) {
    __nv_bfloat162 v = __floats2bfloat162_rn(lo, hi);
    return *reinterpret_cast<uint32_t*>(&v);
}
__device__ __forceinline__ float bf16_round(float x) { return __bfloat162float(__float2bfloat16_rn(x)); }

template <int BK>
__device__ __forceinline__ void mainloop_consumer(float (&acc)[128], uint32_t smem_base, uint32_t full_bar,
                                                  uint32_t empty_bar, int wg, bool leader) {
    constexpr int KT = 1024 / BK;
    constexpr int STAGE = (BM + BN) * BK * 2;
    constexpr int ABYTES = BM * BK * 2;
#pragma unroll 1
    for (int it = 0; it < KT; ++it) {
        const int s = it % STAGES;
        mbar_wait(full_bar + 8 * s, (it / STAGES) & 1);
        const uint32_t a_addr = smem_base + s * STAGE + wg * (64 * BK * 2);
        const uint32_t b_addr = smem_base + s * STAGE + ABYTES;
        wgmma_fence();
#pragma unroll
        for (int k = 0; k < BK / 16; ++k) {
            uint64_t da = make_desc(a_addr + k * 32, 16, 8 * BK * 2, BK == 64 ? 1 : 2);
            uint64_t db = make_desc(b_addr + k * 2048, BK * 128, 1024);
            wgmma_m64n256k16(acc, da, db, (it | k) != 0);
        }
        wgmma_commit();
        if (it > 0) {
            wgmma_wait<1>();
            if (leader) {
                mbar_arrive_cluster(empty_bar + 8 * ((it - 1) % STAGES), 0);
                mbar_arrive_cluster(empty_bar + 8 * ((it - 1) % STAGES), 1);
            }
        }
    }
    wgmma_wait<0>();
}

template <int BK, bool PDL_WAIT>
__device__ __forceinline__ void mainloop_producer(uint32_t smem_base, uint32_t full_bar, uint32_t empty_bar,
                                                  const CUtensorMap* tmA, const CUtensorMap* tmB, int a_k0, int a_row,
                                                  int b_col, int b_k0, uint32_t crank) {
    constexpr int KT = 1024 / BK;
    constexpr int STAGE = (BM + BN) * BK * 2;
    constexpr int ABYTES = BM * BK * 2;
    for (int it = 0; it < KT; ++it) {
        const int s = it % STAGES;
        mbar_wait(empty_bar + 8 * s, ((it / STAGES) & 1) ^ 1);
        const uint32_t st = smem_base + s * STAGE;
        mbar_expect_tx(full_bar + 8 * s, STAGE);
#pragma unroll
        for (int jj = 0; jj < 2; ++jj) {
            const int j = crank * 2 + jj;
            tma_load_2d_mc(st + ABYTES + j * (BK * 128), tmB, full_bar + 8 * s, b_col + j * 64, b_k0 + it * BK,
                           (uint16_t)3);
        }
        if (PDL_WAIT && it == 0) asm volatile("griddepcontrol.wait;" ::: "memory");
        tma_load_2d(st, tmA, full_bar + 8 * s, a_k0 + it * BK, a_row);
    }
}

__global__ void __cluster_dims__(2, 1, 1) __launch_bounds__(NTHREADS, 1)
qproj_attn_kernel(const __grid_constant__ CUtensorMap tmX0, const __grid_constant__ CUtensorMap tmX1,
                  const __grid_constant__ CUtensorMap tmW0, const __grid_constant__ CUtensorMap tmW1,
                  const __grid_constant__ CUtensorMap tmK0, const __grid_constant__ CUtensorMap tmK1,
                  const __grid_constant__ CUtensorMap tmV0, const __grid_constant__ CUtensorMap tmV1,
                  const __grid_constant__ CUtensorMap tmOst) {
    extern __shared__ uint8_t smem_raw[];
    const uint32_t smem_base = (smem_u32(smem_raw) + 1023) & ~1023u;
    const uint32_t full_bar = smem_base + K1_BAR_OFF;
    const uint32_t empty_bar = full_bar + 8 * STAGES;
    const uint32_t kv_bar = empty_bar + 8 * STAGES;
    const uint32_t kv_base = smem_base + K1_KV_OFF;

    const int idx = blockIdx.x;
    const int blk = idx >> 6;
    const int nt = (idx & 63) >> 2;
    const int mt = idx & 3;
    const uint32_t crank = idx & 1;
    const int warp = threadIdx.x >> 5;
    const int lane = threadIdx.x & 31;

    if (threadIdx.x == 0) {
        for (int s = 0; s < STAGES; ++s) {
            mbar_init(full_bar + 8 * s, 1);
            mbar_init(empty_bar + 8 * s, 4);
        }
        mbar_init(kv_bar, 1);
        asm volatile("fence.mbarrier_init.release.cluster;" ::: "memory");
    }
    __syncthreads();
    STAMP(0, 0);
    cluster_sync_all();
    STAMP(0, 1);
    asm volatile("griddepcontrol.launch_dependents;" ::: "memory");

    if (warp >= 8) {
        if (warp == 8 && lane == 0) {
            const CUtensorMap* tmK = blk ? &tmK1 : &tmK0;
            const CUtensorMap* tmV = blk ? &tmV1 : &tmV0;
            mbar_expect_tx(kv_bar, 16 * BOX_BYTES);
            for (int e = 0; e < 16; ++e) {
                const int kv = e >> 3, bl = (e >> 1) & 3, half = e & 1;
                const int row0 = ((mt * 4 + bl) * 32 + nt * 2) * 32;
                tma_load_2d(kv_base + e * BOX_BYTES, kv ? tmV : tmK, kv_bar, half * 64, row0);
            }
            mainloop_producer<K1_BK, false>(smem_base, full_bar, empty_bar, blk ? &tmX1 : &tmX0,
                                            blk ? &tmW1 : &tmW0, 0, mt * BM, nt * BN, 0, crank);
        }
    } else {
        const int wg = warp >> 2;
        const bool leader = (threadIdx.x & 127) == 0;
        float acc[128];
        mainloop_consumer<K1_BK>(acc, smem_base, full_bar, empty_bar, wg, leader);

        STAMP(0, 2);
        uint32_t qf[64];
#pragma unroll
        for (int i = 0; i < 64; ++i) qf[i] = pack_bf16(acc[2 * i], acc[2 * i + 1]);

        mbar_wait(kv_bar, 0);
        STAMP(0, 3);
        const int bl = wg * 2 + ((warp & 3) >> 1);
        const uint32_t kbase = kv_base + (bl * 2) * BOX_BYTES;
        const uint32_t vbase = kv_base + (8 + bl * 2) * BOX_BYTES;
        const int orow = wg * 64 + (warp & 3) * 16 + (lane & 7) + ((lane >> 3) & 1) * 8;
        const uint32_t ost = smem_base + orow * 128;

#pragma unroll
        for (int hh = 0; hh < 2; ++hh) {
            float sc[4][4];
#pragma unroll
            for (int n = 0; n < 4; ++n)
#pragma unroll
                for (int c = 0; c < 4; ++c) sc[n][c] = 0.f;
#pragma unroll
            for (int kk = 0; kk < 8; kk += 2) {
                const int chunk = 2 * kk + (lane >> 3);
                const int half = chunk >> 3, c8 = chunk & 7;
#pragma unroll
                for (int n = 0; n < 4; ++n) {
                    const int r = hh * 32 + n * 8 + (lane & 7);
                    const uint32_t addr = kbase + half * BOX_BYTES + r * 128 + ((c8 ^ (r & 7)) << 4);
                    uint32_t b0, b1, b2, b3;
                    ldsm_x4(addr, b0, b1, b2, b3);
                    const int q0 = hh * 32 + kk * 4;
                    mma_bf16(sc[n], qf[q0 + 0], qf[q0 + 1], qf[q0 + 2], qf[q0 + 3], b0, b1);
                    mma_bf16(sc[n], qf[q0 + 4], qf[q0 + 5], qf[q0 + 6], qf[q0 + 7], b2, b3);
                }
            }
            const float scale = 0.08838834764831845f;
            float m0 = -INFINITY, m1 = -INFINITY;
#pragma unroll
            for (int n = 0; n < 4; ++n) {
#pragma unroll
                for (int c = 0; c < 4; ++c) sc[n][c] = bf16_round(bf16_round(sc[n][c]) * scale);
                m0 = fmaxf(m0, fmaxf(sc[n][0], sc[n][1]));
                m1 = fmaxf(m1, fmaxf(sc[n][2], sc[n][3]));
            }
            m0 = fmaxf(m0, __shfl_xor_sync(0xffffffffu, m0, 1));
            m0 = fmaxf(m0, __shfl_xor_sync(0xffffffffu, m0, 2));
            m1 = fmaxf(m1, __shfl_xor_sync(0xffffffffu, m1, 1));
            m1 = fmaxf(m1, __shfl_xor_sync(0xffffffffu, m1, 2));
            float s0 = 0.f, s1 = 0.f;
#pragma unroll
            for (int n = 0; n < 4; ++n) {
                sc[n][0] = __expf(sc[n][0] - m0);
                sc[n][1] = __expf(sc[n][1] - m0);
                sc[n][2] = __expf(sc[n][2] - m1);
                sc[n][3] = __expf(sc[n][3] - m1);
                s0 += sc[n][0] + sc[n][1];
                s1 += sc[n][2] + sc[n][3];
            }
            s0 += __shfl_xor_sync(0xffffffffu, s0, 1);
            s0 += __shfl_xor_sync(0xffffffffu, s0, 2);
            s1 += __shfl_xor_sync(0xffffffffu, s1, 1);
            s1 += __shfl_xor_sync(0xffffffffu, s1, 2);
            const float i0 = 1.f / s0, i1 = 1.f / s1;
            uint32_t pf[2][4];
#pragma unroll
            for (int kk = 0; kk < 2; ++kk) {
                pf[kk][0] = pack_bf16(sc[2 * kk][0] * i0, sc[2 * kk][1] * i0);
                pf[kk][1] = pack_bf16(sc[2 * kk][2] * i1, sc[2 * kk][3] * i1);
                pf[kk][2] = pack_bf16(sc[2 * kk + 1][0] * i0, sc[2 * kk + 1][1] * i0);
                pf[kk][3] = pack_bf16(sc[2 * kk + 1][2] * i1, sc[2 * kk + 1][3] * i1);
            }
#pragma unroll
            for (int n = 0; n < 16; n += 2) {
                const int r = hh * 32 + lane;
                const int half = n >> 3, c8 = n & 7;
                const uint32_t addr = vbase + half * BOX_BYTES + r * 128;
                uint32_t b0, b1, b2, b3, b4, b5, b6, b7;
                ldsm_x4_t(addr + ((c8 ^ (r & 7)) << 4), b0, b1, b2, b3);
                ldsm_x4_t(addr + (((c8 + 1) ^ (r & 7)) << 4), b4, b5, b6, b7);
                float oa[4] = {0.f, 0.f, 0.f, 0.f}, ob[4] = {0.f, 0.f, 0.f, 0.f};
                mma_bf16(oa, pf[0][0], pf[0][1], pf[0][2], pf[0][3], b0, b1);
                mma_bf16(ob, pf[0][0], pf[0][1], pf[0][2], pf[0][3], b4, b5);
                mma_bf16(oa, pf[1][0], pf[1][1], pf[1][2], pf[1][3], b2, b3);
                mma_bf16(ob, pf[1][0], pf[1][1], pf[1][2], pf[1][3], b6, b7);
                const int cn = c8 + (lane >> 4);
                stsm_x4(ost + (hh * 2 + half) * 16384 + ((cn ^ (orow & 7)) << 4), pack_bf16(oa[0], oa[1]),
                        pack_bf16(oa[2], oa[3]), pack_bf16(ob[0], ob[1]), pack_bf16(ob[2], ob[3]));
            }
        }
        fence_async_smem();
        wg_bar(wg);
        if (leader) {
#pragma unroll
            for (int c = 0; c < 4; ++c)
                tma_store_2d(&tmOst, smem_base + c * 16384 + wg * 8192, nt * 256 + c * 64, blk * 512 + mt * BM + wg * 64);
            tma_store_commit_wait();
        }
    }
    STAMP(0, 4);
    cluster_sync_all();
}

__device__ float4 g_red[32 * 4 * 4 * 8 * 256];
__device__ unsigned int g_flag[32 * 4 * 2];

__global__ void __cluster_dims__(2, 1, 1) __launch_bounds__(NTHREADS, 1)
oproj_kernel(const __grid_constant__ CUtensorMap tmO, const __grid_constant__ CUtensorMap tmW0,
             const __grid_constant__ CUtensorMap tmW1, const __grid_constant__ CUtensorMap tmOut) {
    extern __shared__ uint8_t smem_raw[];
    const uint32_t smem_base = (smem_u32(smem_raw) + 1023) & ~1023u;
    const uint32_t full_bar = smem_base + K2_BAR_OFF;
    const uint32_t empty_bar = full_bar + 8 * STAGES;

    const int idx = blockIdx.x;
    const int blk = idx >> 6;
    const int ks = (idx >> 4) & 3;
    const int nt = (idx >> 2) & 3;
    const int mt = idx & 3;
    const uint32_t crank = idx & 1;
    const int tile = blk * 16 + mt * 4 + nt;
    const int warp = threadIdx.x >> 5;

    if (threadIdx.x == 0) {
        for (int s = 0; s < STAGES; ++s) {
            mbar_init(full_bar + 8 * s, 1);
            mbar_init(empty_bar + 8 * s, 4);
        }
        asm volatile("fence.mbarrier_init.release.cluster;" ::: "memory");
    }
    __syncthreads();
    STAMP(1, 0);
    cluster_sync_all();
    STAMP(1, 1);

    if (warp >= 8) {
        if (warp == 8 && (threadIdx.x & 31) == 0) {
            mainloop_producer<K2_BK, true>(smem_base, full_bar, empty_bar, &tmO, blk ? &tmW1 : &tmW0, ks * 1024,
                                           blk * 512 + mt * BM, nt * BN, ks * 1024, crank);
        }
    } else {
        const int wg = warp >> 2;
        const bool leader = (threadIdx.x & 127) == 0;
        float acc[128];
        mainloop_consumer<K2_BK>(acc, smem_base, full_bar, empty_bar, wg, leader);

        STAMP(1, 2);
        const int tid = threadIdx.x;
#pragma unroll
        for (int j = 0; j < 4; ++j) {
            if (j != ks) {
                float4* dst = g_red + ((size_t)((tile * 4 + j) * 4 + ks) * 8) * 256 + tid;
#pragma unroll
                for (int i = 0; i < 8; ++i)
                    __stcg(dst + i * 256, make_float4(acc[j * 32 + i * 4 + 0], acc[j * 32 + i * 4 + 1],
                                                      acc[j * 32 + i * 4 + 2], acc[j * 32 + i * 4 + 3]));
            }
        }
        __threadfence();
        wg_bar(wg);
        if (leader) {
#pragma unroll
            for (int j = 0; j < 4; ++j)
                if (j != ks) atomicAdd(&g_flag[(tile * 4 + j) * 2 + wg], 1u);
            volatile unsigned int* f = &g_flag[(tile * 4 + ks) * 2 + wg];
            unsigned int spins = 0;
            while (*f < 3u && ++spins < (1u << 26)) { }
            *f = 0;
            __threadfence();
        }
        wg_bar(wg);
        STAMP(1, 3);
        const int lane = tid & 31;
        const int orow = wg * 64 + (warp & 3) * 16 + (lane & 7) + ((lane >> 3) & 1) * 8;
        const uint32_t ost = smem_base + orow * 128;
#pragma unroll
        for (int j = 0; j < 4; ++j) {
            if (j == ks) {
#pragma unroll
                for (int i = 0; i < 8; i += 2) {
                    uint32_t pk[4];
#pragma unroll
                    for (int u = 0; u < 2; ++u) {
                        float v0 = acc[j * 32 + (i + u) * 4 + 0], v1 = acc[j * 32 + (i + u) * 4 + 1];
                        float v2 = acc[j * 32 + (i + u) * 4 + 2], v3 = acc[j * 32 + (i + u) * 4 + 3];
#pragma unroll
                        for (int sl = 0; sl < 4; ++sl) {
                            if (sl != j) {
                                float4 r = __ldcg(g_red + ((size_t)((tile * 4 + j) * 4 + sl) * 8 + i + u) * 256 + tid);
                                v0 += r.x; v1 += r.y; v2 += r.z; v3 += r.w;
                            }
                        }
                        pk[u * 2 + 0] = pack_bf16(v0, v1);
                        pk[u * 2 + 1] = pack_bf16(v2, v3);
                    }
                    const int cn = i + (lane >> 4);
                    stsm_x4(ost + ((cn ^ (orow & 7)) << 4), pk[0], pk[1], pk[2], pk[3]);
                }
            }
        }
        fence_async_smem();
        wg_bar(wg);
        if (leader) {
            tma_store_2d(&tmOut, smem_base + wg * 8192, blk * 1024 + nt * 256 + ks * 64, mt * BM + wg * 64);
            tma_store_commit_wait();
        }
    }
    STAMP(1, 4);
    cluster_sync_all();
}

typedef CUresult (*EncodeFn)(CUtensorMap*, CUtensorMapDataType, cuuint32_t, void*, const cuuint64_t*,
                             const cuuint64_t*, const cuuint32_t*, const cuuint32_t*, CUtensorMapInterleave,
                             CUtensorMapSwizzle, CUtensorMapL2promotion, CUtensorMapFloatOOBfill);

EncodeFn get_encode() {
    static EncodeFn fn = nullptr;
    if (!fn) {
        void* p = nullptr;
        cudaDriverEntryPointQueryResult qres;
        cudaGetDriverEntryPoint("cuTensorMapEncodeTiled", &p, cudaEnableDefault, &qres);
        fn = (EncodeFn)p;
    }
    return fn;
}

CUtensorMap make_map(const void* ptr, uint64_t inner, uint64_t outer, uint32_t box_inner, uint32_t box_outer,
                     CUtensorMapSwizzle swz = CU_TENSOR_MAP_SWIZZLE_128B) {
    CUtensorMap m;
    cuuint64_t dims[2] = {inner, outer};
    cuuint64_t strides[1] = {inner * 2};
    cuuint32_t box[2] = {box_inner, box_outer};
    cuuint32_t estr[2] = {1, 1};
    get_encode()(&m, CU_TENSOR_MAP_DATA_TYPE_BFLOAT16, 2, const_cast<void*>(ptr), dims, strides, box, estr,
                 CU_TENSOR_MAP_INTERLEAVE_NONE, swz, CU_TENSOR_MAP_L2_PROMOTION_L2_256B,
                 CU_TENSOR_MAP_FLOAT_OOB_FILL_NONE);
    return m;
}

}

extern "C" void kernel_launch(void* const* d_in, const int* in_sizes, int n_in, void* d_out, int out_size) {
    (void)in_sizes; (void)n_in; (void)out_size;
    void* o_scratch = nullptr;
    cudaGetSymbolAddress(&o_scratch, g_o);

    CUtensorMap tmX[2], tmWq[2], tmK[2], tmV[2], tmWo[2];
    for (int b = 0; b < 2; ++b) {
        tmX[b] = make_map(d_in[b * 5 + 0], 1024, 512, K1_BK, 128, CU_TENSOR_MAP_SWIZZLE_64B);
        tmK[b] = make_map(d_in[b * 5 + 1], 128, 16384, 64, 64);
        tmV[b] = make_map(d_in[b * 5 + 2], 128, 16384, 64, 64);
        tmWq[b] = make_map(d_in[b * 5 + 3], 4096, 1024, 64, K1_BK);
        tmWo[b] = make_map(d_in[b * 5 + 4], 1024, 4096, 64, K2_BK);
    }
    CUtensorMap tmO = make_map(o_scratch, 4096, 1024, 64, 128);
    CUtensorMap tmOst = make_map(o_scratch, 4096, 1024, 64, 64);
    CUtensorMap tmOut = make_map(d_out, 2048, 512, 64, 64);

    static bool attr_done = false;
    if (!attr_done) {
        cudaFuncSetAttribute(qproj_attn_kernel, cudaFuncAttributeMaxDynamicSharedMemorySize, K1_SMEM);
        cudaFuncSetAttribute(oproj_kernel, cudaFuncAttributeMaxDynamicSharedMemorySize, K2_SMEM);
        attr_done = true;
    }
    qproj_attn_kernel<<<128, NTHREADS, K1_SMEM>>>(tmX[0], tmX[1], tmWq[0], tmWq[1], tmK[0], tmK[1], tmV[0], tmV[1],
                                                  tmOst);
    cudaLaunchConfig_t cfg = {};
    cfg.gridDim = dim3(128);
    cfg.blockDim = dim3(NTHREADS);
    cfg.dynamicSmemBytes = K2_SMEM;
    cfg.stream = cudaStreamPerThread;
    cudaLaunchAttribute at[1];
    at[0].id = cudaLaunchAttributeProgrammaticStreamSerialization;
    at[0].val.programmaticStreamSerializationAllowed = 1;
    cfg.attrs = at;
    cfg.numAttrs = 1;
    cudaLaunchKernelEx(&cfg, oproj_kernel, tmO, tmWo[0], tmWo[1], tmOut);
}
```

```cpp
#include <cuda_runtime.h>
#include <cuda_bf16.h>
#include <cuda.h>
#include <stdint.h>

namespace {

constexpr int BM = 128, BN = 256;
constexpr int STAGES = 4;
constexpr int BOX_BYTES = 64 * 64 * 2;
constexpr int NTHREADS = 384;
constexpr int K1_BK = 32;
constexpr int K1_STAGE = (BM + BN) * K1_BK * 2;
constexpr int K1_KV_OFF = STAGES * K1_STAGE;
constexpr int K1_BAR_OFF = K1_KV_OFF + 16 * BOX_BYTES;
constexpr int K1_SMEM = K1_BAR_OFF + 128 + 1024;
constexpr int K2_BK = 64;
constexpr int K2_STAGE = (BM + BN) * K2_BK * 2;
constexpr int K2_BAR_OFF = STAGES * K2_STAGE;
constexpr int K2_SMEM = K2_BAR_OFF + 128 + 1024;

__device__ __nv_bfloat16 g_o[2 * 512 * 4096];

#define STAMP(k, i) do { } while (0)

__device__ __forceinline__ uint32_t smem_u32(const void* p) {
    return (uint32_t)__cvta_generic_to_shared(p);
}
__device__ __forceinline__ void mbar_init(uint32_t bar, uint32_t count) {
    asm volatile("mbarrier.init.shared::cta.b64 [%0], %1;" ::"r"(bar), "r"(count));
}
__device__ __forceinline__ void mbar_expect_tx(uint32_t bar, uint32_t bytes) {
    asm volatile("mbarrier.arrive.expect_tx.shared::cta.b64 _, [%0], %1;" ::"r"(bar), "r"(bytes) : "memory");
}
__device__ __forceinline__ void mbar_arrive(uint32_t bar) {
    asm volatile("mbarrier.arrive.shared::cta.b64 _, [%0];" ::"r"(bar) : "memory");
}
__device__ __forceinline__ void mbar_wait(uint32_t bar, uint32_t parity) {
    asm volatile(
        "{\n"
        ".reg .pred P1;\n"
        "LAB_WAIT:\n"
        "mbarrier.try_wait.parity.shared::cta.b64 P1, [%0], %1;\n"
        "@P1 bra DONE;\n"
        "bra LAB_WAIT;\n"
        "DONE:\n"
        "}\n" ::"r"(bar), "r"(parity) : "memory");
}
__device__ __forceinline__ void tma_load_2d(uint32_t dst, const CUtensorMap* tm, uint32_t bar, int c0, int c1) {
    asm volatile(
        "cp.async.bulk.tensor.2d.shared::cluster.global.mbarrier::complete_tx::bytes [%0], [%1, {%3, %4}], [%2];"
        ::"r"(dst), "l"(tm), "r"(bar), "r"(c0), "r"(c1) : "memory");
}
__device__ __forceinline__ void tma_load_2d_mc(uint32_t dst, const CUtensorMap* tm, uint32_t bar, int c0, int c1,
                                               uint16_t mask) {
    asm volatile(
        "cp.async.bulk.tensor.2d.shared::cluster.global.mbarrier::complete_tx::bytes.multicast::cluster "
        "[%0], [%1, {%3, %4}], [%2], %5;"
        ::"r"(dst), "l"(tm), "r"(bar), "r"(c0), "r"(c1), "h"(mask) : "memory");
}
__device__ __forceinline__ void mbar_arrive_cluster(uint32_t bar, uint32_t rank) {
    asm volatile(
        "{\n"
        ".reg .b32 ra;\n"
        "mapa.shared::cluster.u32 ra, %0, %1;\n"
        "mbarrier.arrive.shared::cluster.b64 _, [ra];\n"
        "}\n" ::"r"(bar), "r"(rank) : "memory");
}
__device__ __forceinline__ void cluster_sync_all() {
    asm volatile("barrier.cluster.arrive.release.aligned;\nbarrier.cluster.wait.acquire.aligned;" ::: "memory");
}
__device__ __forceinline__ void tma_store_2d(const CUtensorMap* tm, uint32_t src, int c0, int c1) {
    asm volatile("cp.async.bulk.tensor.2d.global.shared::cta.bulk_group [%0, {%2, %3}], [%1];"
                 ::"l"(tm), "r"(src), "r"(c0), "r"(c1) : "memory");
}
__device__ __forceinline__ void tma_store_commit_wait() {
    asm volatile("cp.async.bulk.commit_group;\ncp.async.bulk.wait_group 0;" ::: "memory");
}
__device__ __forceinline__ void fence_async_smem() { asm volatile("fence.proxy.async.shared::cta;" ::: "memory"); }
__device__ __forceinline__ void stsm_x4(uint32_t addr, uint32_t r0, uint32_t r1, uint32_t r2, uint32_t r3) {
    asm volatile("stmatrix.sync.aligned.m8n8.x4.shared.b16 [%0], {%1, %2, %3, %4};"
                 ::"r"(addr), "r"(r0), "r"(r1), "r"(r2), "r"(r3) : "memory");
}
__device__ __forceinline__ void wg_bar(int wg) { asm volatile("bar.sync %0, 128;" ::"r"(1 + wg) : "memory"); }
__device__ __forceinline__ void wgmma_fence() { asm volatile("wgmma.fence.sync.aligned;" ::: "memory"); }
__device__ __forceinline__ void wgmma_commit() { asm volatile("wgmma.commit_group.sync.aligned;" ::: "memory"); }
template <int N>
__device__ __forceinline__ void wgmma_wait() { asm volatile("wgmma.wait_group.sync.aligned %0;" ::"n"(N) : "memory"); }

__device__ __forceinline__ uint64_t make_desc(uint32_t addr, uint32_t lbo, uint32_t sbo, uint32_t swz = 1) {
    uint64_t d = 0;
    d |= (uint64_t)((addr & 0x3FFFF) >> 4);
    d |= (uint64_t)((lbo >> 4) & 0x3FFF) << 16;
    d |= (uint64_t)((sbo >> 4) & 0x3FFF) << 32;
    d |= (uint64_t)swz << 62;
    return d;
}

__device__ __forceinline__ void wgmma_m64n256k16(float (&d)[128], uint64_t da, uint64_t db, int scale_d) {
    asm volatile(
        "{\n"
        ".reg .pred p;\n"
        "setp.ne.b32 p, %130, 0;\n"
        "wgmma.mma_async.sync.aligned.m64n256k16.f32.bf16.bf16 "
        "{%0, %1, %2, %3, %4, %5, %6, %7, %8, %9, %10, %11, %12, %13, %14, %15, "
        "%16, %17, %18, %19, %20, %21, %22, %23, %24, %25, %26, %27, %28, %29, %30, %31, "
        "%32, %33, %34, %35, %36, %37, %38, %39, %40, %41, %42, %43, %44, %45, %46, %47, "
        "%48, %49, %50, %51, %52, %53, %54, %55, %56, %57, %58, %59, %60, %61, %62, %63, "
        "%64, %65, %66, %67, %68, %69, %70, %71, %72, %73, %74, %75, %76, %77, %78, %79, "
        "%80, %81, %82, %83, %84, %85, %86, %87, %88, %89, %90, %91, %92, %93, %94, %95, "
        "%96, %97, %98, %99, %100, %101, %102, %103, %104, %105, %106, %107, %108, %109, %110, %111, "
        "%112, %113, %114, %115, %116, %117, %118, %119, %120, %121, %122, %123, %124, %125, %126, %127}, "
        "%128, %129, p, 1, 1, 0, 1;\n"
        "}\n"
        : "+f"(d[0]), "+f"(d[1]), "+f"(d[2]), "+f"(d[3]), "+f"(d[4]), "+f"(d[5]), "+f"(d[6]), "+f"(d[7]),
          "+f"(d[8]), "+f"(d[9]), "+f"(d[10]), "+f"(d[11]), "+f"(d[12]), "+f"(d[13]), "+f"(d[14]), "+f"(d[15]),
          "+f"(d[16]), "+f"(d[17]), "+f"(d[18]), "+f"(d[19]), "+f"(d[20]), "+f"(d[21]), "+f"(d[22]), "+f"(d[23]),
          "+f"(d[24]), "+f"(d[25]), "+f"(d[26]), "+f"(d[27]), "+f"(d[28]), "+f"(d[29]), "+f"(d[30]), "+f"(d[31]),
          "+f"(d[32]), "+f"(d[33]), "+f"(d[34]), "+f"(d[35]), "+f"(d[36]), "+f"(d[37]), "+f"(d[38]), "+f"(d[39]),
          "+f"(d[40]), "+f"(d[41]), "+f"(d[42]), "+f"(d[43]), "+f"(d[44]), "+f"(d[45]), "+f"(d[46]), "+f"(d[47]),
          "+f"(d[48]), "+f"(d[49]), "+f"(d[50]), "+f"(d[51]), "+f"(d[52]), "+f"(d[53]), "+f"(d[54]), "+f"(d[55]),
          "+f"(d[56]), "+f"(d[57]), "+f"(d[58]), "+f"(d[59]), "+f"(d[60]), "+f"(d[61]), "+f"(d[62]), "+f"(d[63]),
          "+f"(d[64]), "+f"(d[65]), "+f"(d[66]), "+f"(d[67]), "+f"(d[68]), "+f"(d[69]), "+f"(d[70]), "+f"(d[71]),
          "+f"(d[72]), "+f"(d[73]), "+f"(d[74]), "+f"(d[75]), "+f"(d[76]), "+f"(d[77]), "+f"(d[78]), "+f"(d[79]),
          "+f"(d[80]), "+f"(d[81]), "+f"(d[82]), "+f"(d[83]), "+f"(d[84]), "+f"(d[85]), "+f"(d[86]), "+f"(d[87]),
          "+f"(d[88]), "+f"(d[89]), "+f"(d[90]), "+f"(d[91]), "+f"(d[92]), "+f"(d[93]), "+f"(d[94]), "+f"(d[95]),
          "+f"(d[96]), "+f"(d[97]), "+f"(d[98]), "+f"(d[99]), "+f"(d[100]), "+f"(d[101]), "+f"(d[102]), "+f"(d[103]),
          "+f"(d[104]), "+f"(d[105]), "+f"(d[106]), "+f"(d[107]), "+f"(d[108]), "+f"(d[109]), "+f"(d[110]), "+f"(d[111]),
          "+f"(d[112]), "+f"(d[113]), "+f"(d[114]), "+f"(d[115]), "+f"(d[116]), "+f"(d[117]), "+f"(d[118]), "+f"(d[119]),
          "+f"(d[120]), "+f"(d[121]), "+f"(d[122]), "+f"(d[123]), "+f"(d[124]), "+f"(d[125]), "+f"(d[126]), "+f"(d[127])
        : "l"(da), "l"(db), "r"(scale_d));
}

__device__ __forceinline__ void ldsm_x4(uint32_t addr, uint32_t& r0, uint32_t& r1, uint32_t& r2, uint32_t& r3) {
    asm volatile("ldmatrix.sync.aligned.m8n8.x4.shared.b16 {%0, %1, %2, %3}, [%4];"
                 : "=r"(r0), "=r"(r1), "=r"(r2), "=r"(r3) : "r"(addr));
}
__device__ __forceinline__ void ldsm_x4_t(uint32_t addr, uint32_t& r0, uint32_t& r1, uint32_t& r2, uint32_t& r3) {
    asm volatile("ldmatrix.sync.aligned.m8n8.x4.trans.shared.b16 {%0, %1, %2, %3}, [%4];"
                 : "=r"(r0), "=r"(r1), "=r"(r2), "=r"(r3) : "r"(addr));
}
__device__ __forceinline__ void mma_bf16(float (&c)[4], uint32_t a0, uint32_t a1, uint32_t a2, uint32_t a3,
                                         uint32_t b0, uint32_t b1) {
    asm volatile(
        "mma.sync.aligned.m16n8k16.row.col.f32.bf16.bf16.f32 {%0, %1, %2, %3}, {%4, %5, %6, %7}, {%8, %9}, "
        "{%0, %1, %2, %3};"
        : "+f"(c[0]), "+f"(c[1]), "+f"(c[2]), "+f"(c[3])
        : "r"(a0), "r"(a1), "r"(a2), "r"(a3), "r"(b0), "r"(b1));
}
__device__ __forceinline__ uint32_t pack_bf16(float lo, float hi) {
    __nv_bfloat162 v = __floats2bfloat162_rn(lo, hi);
    return *reinterpret_cast<uint32_t*>(&v);
}
__device__ __forceinline__ float bf16_round(float x) { return __bfloat162float(__float2bfloat16_rn(x)); }

template <int BK>
__device__ __forceinline__ void mainloop_consumer(float (&acc)[128], uint32_t smem_base, uint32_t full_bar,
                                                  uint32_t empty_bar, int wg, bool leader) {
    constexpr int KT = 1024 / BK;
    constexpr int STAGE = (BM + BN) * BK * 2;
    constexpr int ABYTES = BM * BK * 2;
#pragma unroll 1
    for (int it = 0; it < KT; ++it) {
        const int s = it % STAGES;
        mbar_wait(full_bar + 8 * s, (it / STAGES) & 1);
        const uint32_t a_addr = smem_base + s * STAGE + wg * (64 * BK * 2);
        const uint32_t b_addr = smem_base + s * STAGE + ABYTES;
        wgmma_fence();
#pragma unroll
        for (int k = 0; k < BK / 16; ++k) {
            uint64_t da = make_desc(a_addr + k * 32, 16, 8 * BK * 2, BK == 64 ? 1 : 2);
            uint64_t db = make_desc(b_addr + k * 2048, BK * 128, 1024);
            wgmma_m64n256k16(acc, da, db, (it | k) != 0);
        }
        wgmma_commit();
        if (it > 0) {
            wgmma_wait<1>();
            if (leader) {
                mbar_arrive_cluster(empty_bar + 8 * ((it - 1) % STAGES), 0);
                mbar_arrive_cluster(empty_bar + 8 * ((it - 1) % STAGES), 1);
            }
        }
    }
    wgmma_wait<0>();
}

template <int BK, bool PDL_WAIT, typename Hook>
__device__ __forceinline__ void mainloop_producer(uint32_t smem_base, uint32_t full_bar, uint32_t empty_bar,
                                                  const CUtensorMap* tmA, const CUtensorMap* tmB, int a_k0, int a_row,
                                                  int b_col, int b_k0, uint32_t crank, Hook hook) {
    constexpr int KT = 1024 / BK;
    constexpr int STAGE = (BM + BN) * BK * 2;
    constexpr int ABYTES = BM * BK * 2;
    for (int it = 0; it < KT; ++it) {
        const int s = it % STAGES;
        mbar_wait(empty_bar + 8 * s, ((it / STAGES) & 1) ^ 1);
        const uint32_t st = smem_base + s * STAGE;
        mbar_expect_tx(full_bar + 8 * s, STAGE);
#pragma unroll
        for (int jj = 0; jj < 2; ++jj) {
            const int j = crank * 2 + jj;
            tma_load_2d_mc(st + ABYTES + j * (BK * 128), tmB, full_bar + 8 * s, b_col + j * 64, b_k0 + it * BK,
                           (uint16_t)3);
        }
        if (PDL_WAIT && it == 0) asm volatile("griddepcontrol.wait;" ::: "memory");
        tma_load_2d(st, tmA, full_bar + 8 * s, a_k0 + it * BK, a_row);
        hook(it);
    }
}

__global__ void __cluster_dims__(2, 1, 1) __launch_bounds__(NTHREADS, 1)
qproj_attn_kernel(const __grid_constant__ CUtensorMap tmX0, const __grid_constant__ CUtensorMap tmX1,
                  const __grid_constant__ CUtensorMap tmW0, const __grid_constant__ CUtensorMap tmW1,
                  const __grid_constant__ CUtensorMap tmK0, const __grid_constant__ CUtensorMap tmK1,
                  const __grid_constant__ CUtensorMap tmV0, const __grid_constant__ CUtensorMap tmV1,
                  const __grid_constant__ CUtensorMap tmOst) {
    extern __shared__ uint8_t smem_raw[];
    const uint32_t smem_base = (smem_u32(smem_raw) + 1023) & ~1023u;
    const uint32_t full_bar = smem_base + K1_BAR_OFF;
    const uint32_t empty_bar = full_bar + 8 * STAGES;
    const uint32_t kv_bar = empty_bar + 8 * STAGES;
    const uint32_t kv_base = smem_base + K1_KV_OFF;

    const int idx = blockIdx.x;
    const int blk = idx >> 6;
    const int nt = (idx & 63) >> 2;
    const int mt = idx & 3;
    const uint32_t crank = idx & 1;
    const int warp = threadIdx.x >> 5;
    const int lane = threadIdx.x & 31;

    if (threadIdx.x == 0) {
        for (int s = 0; s < STAGES; ++s) {
            mbar_init(full_bar + 8 * s, 1);
            mbar_init(empty_bar + 8 * s, 4);
        }
        mbar_init(kv_bar, 1);
        asm volatile("fence.mbarrier_init.release.cluster;" ::: "memory");
    }
    __syncthreads();
    STAMP(0, 0);
    cluster_sync_all();
    STAMP(0, 1);
    asm volatile("griddepcontrol.launch_dependents;" ::: "memory");

    if (warp >= 8) {
        if (warp == 8 && lane == 0) {
            const CUtensorMap* tmK = blk ? &tmK1 : &tmK0;
            const CUtensorMap* tmV = blk ? &tmV1 : &tmV0;
            mbar_expect_tx(kv_bar, 16 * BOX_BYTES);
            mainloop_producer<K1_BK, false>(
                smem_base, full_bar, empty_bar, blk ? &tmX1 : &tmX0, blk ? &tmW1 : &tmW0, 0, mt * BM, nt * BN, 0, crank,
                [&](int it) {
                    const int e = it - 3;
                    if (e >= 0 && e < 16) {
                        const int kv = e >> 3, bl = (e >> 1) & 3, half = e & 1;
                        const int row0 = ((mt * 4 + bl) * 32 + nt * 2) * 32;
                        tma_load_2d(kv_base + e * BOX_BYTES, kv ? tmV : tmK, kv_bar, half * 64, row0);
                    }
                });
        }
    } else {
        const int wg = warp >> 2;
        const bool leader = (threadIdx.x & 127) == 0;
        float acc[128];
        mainloop_consumer<K1_BK>(acc, smem_base, full_bar, empty_bar, wg, leader);

        STAMP(0, 2);
        uint32_t qf[64];
#pragma unroll
        for (int i = 0; i < 64; ++i) qf[i] = pack_bf16(acc[2 * i], acc[2 * i + 1]);

        mbar_wait(kv_bar, 0);
        STAMP(0, 3);
        const int bl = wg * 2 + ((warp & 3) >> 1);
        const uint32_t kbase = kv_base + (bl * 2) * BOX_BYTES;
        const uint32_t vbase = kv_base + (8 + bl * 2) * BOX_BYTES;
        const int orow = wg * 64 + (warp & 3) * 16 + (lane & 7) + ((lane >> 3) & 1) * 8;
        const uint32_t ost = smem_base + orow * 128;

        float sc[2][4][4];
#pragma unroll
        for (int hh = 0; hh < 2; ++hh)
#pragma unroll
            for (int n = 0; n < 4; ++n)
#pragma unroll
                for (int c = 0; c < 4; ++c) sc[hh][n][c] = 0.f;
#pragma unroll
        for (int kk = 0; kk < 8; kk += 2) {
            const int chunk = 2 * kk + (lane >> 3);
            const int half = chunk >> 3, c8 = chunk & 7;
            uint32_t kb[2][4][4];
#pragma unroll
            for (int hh = 0; hh < 2; ++hh)
#pragma unroll
                for (int n = 0; n < 4; ++n) {
                    const int r = hh * 32 + n * 8 + (lane & 7);
                    ldsm_x4(kbase + half * BOX_BYTES + r * 128 + ((c8 ^ (r & 7)) << 4), kb[hh][n][0], kb[hh][n][1],
                            kb[hh][n][2], kb[hh][n][3]);
                }
#pragma unroll
            for (int u = 0; u < 2; ++u)
#pragma unroll
                for (int hh = 0; hh < 2; ++hh)
#pragma unroll
                    for (int n = 0; n < 4; ++n) {
                        const int q0 = hh * 32 + (kk + u) * 4;
                        mma_bf16(sc[hh][n], qf[q0 + 0], qf[q0 + 1], qf[q0 + 2], qf[q0 + 3], kb[hh][n][2 * u],
                                 kb[hh][n][2 * u + 1]);
                    }
        }
        uint32_t pf[2][2][4];
#pragma unroll
        for (int hh = 0; hh < 2; ++hh) {
            const float scale = 0.08838834764831845f;
            float m0 = -INFINITY, m1 = -INFINITY;
#pragma unroll
            for (int n = 0; n < 4; ++n) {
#pragma unroll
                for (int c = 0; c < 4; ++c) sc[hh][n][c] = bf16_round(bf16_round(sc[hh][n][c]) * scale);
                m0 = fmaxf(m0, fmaxf(sc[hh][n][0], sc[hh][n][1]));
                m1 = fmaxf(m1, fmaxf(sc[hh][n][2], sc[hh][n][3]));
            }
            m0 = fmaxf(m0, __shfl_xor_sync(0xffffffffu, m0, 1));
            m1 = fmaxf(m1, __shfl_xor_sync(0xffffffffu, m1, 1));
            m0 = fmaxf(m0, __shfl_xor_sync(0xffffffffu, m0, 2));
            m1 = fmaxf(m1, __shfl_xor_sync(0xffffffffu, m1, 2));
            float s0 = 0.f, s1 = 0.f;
#pragma unroll
            for (int n = 0; n < 4; ++n) {
                sc[hh][n][0] = __expf(sc[hh][n][0] - m0);
                sc[hh][n][1] = __expf(sc[hh][n][1] - m0);
                sc[hh][n][2] = __expf(sc[hh][n][2] - m1);
                sc[hh][n][3] = __expf(sc[hh][n][3] - m1);
                s0 += sc[hh][n][0] + sc[hh][n][1];
                s1 += sc[hh][n][2] + sc[hh][n][3];
            }
            s0 += __shfl_xor_sync(0xffffffffu, s0, 1);
            s1 += __shfl_xor_sync(0xffffffffu, s1, 1);
            s0 += __shfl_xor_sync(0xffffffffu, s0, 2);
            s1 += __shfl_xor_sync(0xffffffffu, s1, 2);
            const float i0 = 1.f / s0, i1 = 1.f / s1;
#pragma unroll
            for (int kk = 0; kk < 2; ++kk) {
                pf[hh][kk][0] = pack_bf16(sc[hh][2 * kk][0] * i0, sc[hh][2 * kk][1] * i0);
                pf[hh][kk][1] = pack_bf16(sc[hh][2 * kk][2] * i1, sc[hh][2 * kk][3] * i1);
                pf[hh][kk][2] = pack_bf16(sc[hh][2 * kk + 1][0] * i0, sc[hh][2 * kk + 1][1] * i0);
                pf[hh][kk][3] = pack_bf16(sc[hh][2 * kk + 1][2] * i1, sc[hh][2 * kk + 1][3] * i1);
            }
        }
#pragma unroll
        for (int hb = 0; hb < 4; ++hb) {
            const int hh = hb >> 1, half = hb & 1;
            const int r = hh * 32 + lane;
            const uint32_t addr = vbase + half * BOX_BYTES + r * 128;
            uint32_t vb[8][4];
#pragma unroll
            for (int c = 0; c < 8; ++c)
                ldsm_x4_t(addr + ((c ^ (r & 7)) << 4), vb[c][0], vb[c][1], vb[c][2], vb[c][3]);
            float oc[8][4];
#pragma unroll
            for (int c = 0; c < 8; ++c) {
                oc[c][0] = oc[c][1] = oc[c][2] = oc[c][3] = 0.f;
                mma_bf16(oc[c], pf[hh][0][0], pf[hh][0][1], pf[hh][0][2], pf[hh][0][3], vb[c][0], vb[c][1]);
            }
#pragma unroll
            for (int c = 0; c < 8; ++c)
                mma_bf16(oc[c], pf[hh][1][0], pf[hh][1][1], pf[hh][1][2], pf[hh][1][3], vb[c][2], vb[c][3]);
#pragma unroll
            for (int c = 0; c < 8; c += 2) {
                const int cn = c + (lane >> 4);
                stsm_x4(ost + hb * 16384 + ((cn ^ (orow & 7)) << 4), pack_bf16(oc[c][0], oc[c][1]),
                        pack_bf16(oc[c][2], oc[c][3]), pack_bf16(oc[c + 1][0], oc[c + 1][1]),
                        pack_bf16(oc[c + 1][2], oc[c + 1][3]));
            }
            if (hb == 1 || hb == 3) {
                fence_async_smem();
                wg_bar(wg);
                if (leader) {
                    tma_store_2d(&tmOst, smem_base + (hb - 1) * 16384 + wg * 8192, nt * 256 + (hb - 1) * 64,
                                 blk * 512 + mt * BM + wg * 64);
                    tma_store_2d(&tmOst, smem_base + hb * 16384 + wg * 8192, nt * 256 + hb * 64,
                                 blk * 512 + mt * BM + wg * 64);
                    asm volatile("cp.async.bulk.commit_group;" ::: "memory");
                }
            }
        }
        if (leader) asm volatile("cp.async.bulk.wait_group 0;" ::: "memory");
    }
    STAMP(0, 4);
    cluster_sync_all();
}

__device__ float4 g_red[32 * 4 * 4 * 8 * 256];
__device__ unsigned int g_flag[32 * 4 * 2];

__global__ void __cluster_dims__(2, 1, 1) __launch_bounds__(NTHREADS, 1)
oproj_kernel(const __grid_constant__ CUtensorMap tmO, const __grid_constant__ CUtensorMap tmW0,
             const __grid_constant__ CUtensorMap tmW1, const __grid_constant__ CUtensorMap tmOut) {
    extern __shared__ uint8_t smem_raw[];
    const uint32_t smem_base = (smem_u32(smem_raw) + 1023) & ~1023u;
    const uint32_t full_bar = smem_base + K2_BAR_OFF;
    const uint32_t empty_bar = full_bar + 8 * STAGES;

    const int idx = blockIdx.x;
    const int blk = idx >> 6;
    const int ks = (idx >> 4) & 3;
    const int nt = (idx >> 2) & 3;
    const int mt = idx & 3;
    const uint32_t crank = idx & 1;
    const int tile = blk * 16 + mt * 4 + nt;
    const int warp = threadIdx.x >> 5;

    if (threadIdx.x == 0) {
        for (int s = 0; s < STAGES; ++s) {
            mbar_init(full_bar + 8 * s, 1);
            mbar_init(empty_bar + 8 * s, 4);
        }
        asm volatile("fence.mbarrier_init.release.cluster;" ::: "memory");
    }
    __syncthreads();
    STAMP(1, 0);
    cluster_sync_all();
    STAMP(1, 1);

    if (warp >= 8) {
        if (warp == 8 && (threadIdx.x & 31) == 0) {
            mainloop_producer<K2_BK, true>(smem_base, full_bar, empty_bar, &tmO, blk ? &tmW1 : &tmW0, ks * 1024,
                                           blk * 512 + mt * BM, nt * BN, ks * 1024, crank, [](int) {});
        }
    } else {
        const int wg = warp >> 2;
        const bool leader = (threadIdx.x & 127) == 0;
        float acc[128];
        mainloop_consumer<K2_BK>(acc, smem_base, full_bar, empty_bar, wg, leader);

        STAMP(1, 2);
        const int tid = threadIdx.x;
#pragma unroll
        for (int j = 0; j < 4; ++j) {
            if (j != ks) {
                float4* dst = g_red + ((size_t)((tile * 4 + j) * 4 + ks) * 8) * 256 + tid;
#pragma unroll
                for (int i = 0; i < 8; ++i)
                    __stcg(dst + i * 256, make_float4(acc[j * 32 + i * 4 + 0], acc[j * 32 + i * 4 + 1],
                                                      acc[j * 32 + i * 4 + 2], acc[j * 32 + i * 4 + 3]));
            }
        }
        __threadfence();
        wg_bar(wg);
        if (leader) {
#pragma unroll
            for (int j = 0; j < 4; ++j)
                if (j != ks) atomicAdd(&g_flag[(tile * 4 + j) * 2 + wg], 1u);
            volatile unsigned int* f = &g_flag[(tile * 4 + ks) * 2 + wg];
            unsigned int spins = 0;
            while (*f < 3u && ++spins < (1u << 26)) { }
            *f = 0;
            __threadfence();
        }
        wg_bar(wg);
        STAMP(1, 3);
        const int lane = tid & 31;
        const int orow = wg * 64 + (warp & 3) * 16 + (lane & 7) + ((lane >> 3) & 1) * 8;
        const uint32_t ost = smem_base + orow * 128;
#pragma unroll
        for (int j = 0; j < 4; ++j) {
            if (j == ks) {
#pragma unroll
                for (int i = 0; i < 8; i += 2) {
                    uint32_t pk[4];
#pragma unroll
                    for (int u = 0; u < 2; ++u) {
                        float v0 = acc[j * 32 + (i + u) * 4 + 0], v1 = acc[j * 32 + (i + u) * 4 + 1];
                        float v2 = acc[j * 32 + (i + u) * 4 + 2], v3 = acc[j * 32 + (i + u) * 4 + 3];
#pragma unroll
                        for (int sl = 0; sl < 4; ++sl) {
                            if (sl != j) {
                                float4 r = __ldcg(g_red + ((size_t)((tile * 4 + j) * 4 + sl) * 8 + i + u) * 256 + tid);
                                v0 += r.x; v1 += r.y; v2 += r.z; v3 += r.w;
                            }
                        }
                        pk[u * 2 + 0] = pack_bf16(v0, v1);
                        pk[u * 2 + 1] = pack_bf16(v2, v3);
                    }
                    const int cn = i + (lane >> 4);
                    stsm_x4(ost + ((cn ^ (orow & 7)) << 4), pk[0], pk[1], pk[2], pk[3]);
                }
            }
        }
        fence_async_smem();
        wg_bar(wg);
        if (leader) {
            tma_store_2d(&tmOut, smem_base + wg * 8192, blk * 1024 + nt * 256 + ks * 64, mt * BM + wg * 64);
            tma_store_commit_wait();
        }
    }
    STAMP(1, 4);
    cluster_sync_all();
}

typedef CUresult (*EncodeFn)(CUtensorMap*, CUtensorMapDataType, cuuint32_t, void*, const cuuint64_t*,
                             const cuuint64_t*, const cuuint32_t*, const cuuint32_t*, CUtensorMapInterleave,
                             CUtensorMapSwizzle, CUtensorMapL2promotion, CUtensorMapFloatOOBfill);

EncodeFn get_encode() {
    static EncodeFn fn = nullptr;
    if (!fn) {
        void* p = nullptr;
        cudaDriverEntryPointQueryResult qres;
        cudaGetDriverEntryPoint("cuTensorMapEncodeTiled", &p, cudaEnableDefault, &qres);
        fn = (EncodeFn)p;
    }
    return fn;
}

CUtensorMap make_map(const void* ptr, uint64_t inner, uint64_t outer, uint32_t box_inner, uint32_t box_outer,
                     CUtensorMapSwizzle swz = CU_TENSOR_MAP_SWIZZLE_128B) {
    CUtensorMap m;
    cuuint64_t dims[2] = {inner, outer};
    cuuint64_t strides[1] = {inner * 2};
    cuuint32_t box[2] = {box_inner, box_outer};
    cuuint32_t estr[2] = {1, 1};
    get_encode()(&m, CU_TENSOR_MAP_DATA_TYPE_BFLOAT16, 2, const_cast<void*>(ptr), dims, strides, box, estr,
                 CU_TENSOR_MAP_INTERLEAVE_NONE, swz, CU_TENSOR_MAP_L2_PROMOTION_L2_256B,
                 CU_TENSOR_MAP_FLOAT_OOB_FILL_NONE);
    return m;
}

}

extern "C" void kernel_launch(void* const* d_in, const int* in_sizes, int n_in, void* d_out, int out_size) {
    (void)in_sizes; (void)n_in; (void)out_size;
    void* o_scratch = nullptr;
    cudaGetSymbolAddress(&o_scratch, g_o);

    CUtensorMap tmX[2], tmWq[2], tmK[2], tmV[2], tmWo[2];
    for (int b = 0; b < 2; ++b) {
        tmX[b] = make_map(d_in[b * 5 + 0], 1024, 512, K1_BK, 128, CU_TENSOR_MAP_SWIZZLE_64B);
        tmK[b] = make_map(d_in[b * 5 + 1], 128, 16384, 64, 64);
        tmV[b] = make_map(d_in[b * 5 + 2], 128, 16384, 64, 64);
        tmWq[b] = make_map(d_in[b * 5 + 3], 4096, 1024, 64, K1_BK);
        tmWo[b] = make_map(d_in[b * 5 + 4], 1024, 4096, 64, K2_BK);
    }
    CUtensorMap tmO = make_map(o_scratch, 4096, 1024, 64, 128);
    CUtensorMap tmOst = make_map(o_scratch, 4096, 1024, 64, 64);
    CUtensorMap tmOut = make_map(d_out, 2048, 512, 64, 64);

    static bool attr_done = false;
    if (!attr_done) {
        cudaFuncSetAttribute(qproj_attn_kernel, cudaFuncAttributeMaxDynamicSharedMemorySize, K1_SMEM);
        cudaFuncSetAttribute(oproj_kernel, cudaFuncAttributeMaxDynamicSharedMemorySize, K2_SMEM);
        attr_done = true;
    }
    qproj_attn_kernel<<<128, NTHREADS, K1_SMEM>>>(tmX[0], tmX[1], tmWq[0], tmWq[1], tmK[0], tmK[1], tmV[0], tmV[1],
                                                  tmOst);
    cudaLaunchConfig_t cfg = {};
    cfg.gridDim = dim3(128);
    cfg.blockDim = dim3(NTHREADS);
    cfg.dynamicSmemBytes = K2_SMEM;
    cfg.stream = cudaStreamPerThread;
    cudaLaunchAttribute at[1];
    at[0].id = cudaLaunchAttributeProgrammaticStreamSerialization;
    at[0].val.programmaticStreamSerializationAllowed = 1;
    cfg.attrs = at;
    cfg.numAttrs = 1;
    cudaLaunchKernelEx(&cfg, oproj_kernel, tmO, tmWo[0], tmWo[1], tmOut);
}
```

```cpp
#include <cuda_runtime.h>
#include <cuda_bf16.h>
#include <cuda.h>
#include <stdint.h>

namespace {

constexpr int BM = 128, BN = 256;
constexpr int STAGES = 4;
constexpr int BOX_BYTES = 64 * 64 * 2;
constexpr int NTHREADS = 384;
constexpr int K1_BK = 32;
constexpr int K1_STAGE = (BM + BN) * K1_BK * 2;
constexpr int K1_KV_OFF = STAGES * K1_STAGE;
constexpr int K1_BAR_OFF = K1_KV_OFF + 16 * BOX_BYTES;
constexpr int K1_SMEM = K1_BAR_OFF + 128 + 1024;
constexpr int K2_BK = 64;
constexpr int K2_STAGE = (BM + BN) * K2_BK * 2;
constexpr int K2_BAR_OFF = STAGES * K2_STAGE;
constexpr int K2_SMEM = K2_BAR_OFF + 128 + 1024;

__device__ __nv_bfloat16 g_o[2 * 512 * 4096];

#define STAMP(k, i) do { } while (0)

__device__ __forceinline__ uint32_t smem_u32(const void* p) {
    return (uint32_t)__cvta_generic_to_shared(p);
}
__device__ __forceinline__ void mbar_init(uint32_t bar, uint32_t count) {
    asm volatile("mbarrier.init.shared::cta.b64 [%0], %1;" ::"r"(bar), "r"(count));
}
__device__ __forceinline__ void mbar_expect_tx(uint32_t bar, uint32_t bytes) {
    asm volatile("mbarrier.arrive.expect_tx.shared::cta.b64 _, [%0], %1;" ::"r"(bar), "r"(bytes) : "memory");
}
__device__ __forceinline__ void mbar_arrive(uint32_t bar) {
    asm volatile("mbarrier.arrive.shared::cta.b64 _, [%0];" ::"r"(bar) : "memory");
}
__device__ __forceinline__ void mbar_wait(uint32_t bar, uint32_t parity) {
    asm volatile(
        "{\n"
        ".reg .pred P1;\n"
        "LAB_WAIT:\n"
        "mbarrier.try_wait.parity.shared::cta.b64 P1, [%0], %1;\n"
        "@P1 bra DONE;\n"
        "bra LAB_WAIT;\n"
        "DONE:\n"
        "}\n" ::"r"(bar), "r"(parity) : "memory");
}
__device__ __forceinline__ void tma_load_2d(uint32_t dst, const CUtensorMap* tm, uint32_t bar, int c0, int c1) {
    asm volatile(
        "cp.async.bulk.tensor.2d.shared::cluster.global.mbarrier::complete_tx::bytes [%0], [%1, {%3, %4}], [%2];"
        ::"r"(dst), "l"(tm), "r"(bar), "r"(c0), "r"(c1) : "memory");
}
__device__ __forceinline__ void tma_load_2d_mc(uint32_t dst, const CUtensorMap* tm, uint32_t bar, int c0, int c1,
                                               uint16_t mask) {
    asm volatile(
        "cp.async.bulk.tensor.2d.shared::cluster.global.mbarrier::complete_tx::bytes.multicast::cluster "
        "[%0], [%1, {%3, %4}], [%2], %5;"
        ::"r"(dst), "l"(tm), "r"(bar), "r"(c0), "r"(c1), "h"(mask) : "memory");
}
__device__ __forceinline__ void mbar_arrive_cluster(uint32_t bar, uint32_t rank) {
    asm volatile(
        "{\n"
        ".reg .b32 ra;\n"
        "mapa.shared::cluster.u32 ra, %0, %1;\n"
        "mbarrier.arrive.shared::cluster.b64 _, [ra];\n"
        "}\n" ::"r"(bar), "r"(rank) : "memory");
}
__device__ __forceinline__ void cluster_sync_all() {
    asm volatile("barrier.cluster.arrive.release.aligned;\nbarrier.cluster.wait.acquire.aligned;" ::: "memory");
}
__device__ __forceinline__ void tma_store_2d(const CUtensorMap* tm, uint32_t src, int c0, int c1) {
    asm volatile("cp.async.bulk.tensor.2d.global.shared::cta.bulk_group [%0, {%2, %3}], [%1];"
                 ::"l"(tm), "r"(src), "r"(c0), "r"(c1) : "memory");
}
__device__ __forceinline__ void tma_store_commit_wait() {
    asm volatile("cp.async.bulk.commit_group;\ncp.async.bulk.wait_group 0;" ::: "memory");
}
__device__ __forceinline__ void fence_async_smem() { asm volatile("fence.proxy.async.shared::cta;" ::: "memory"); }
__device__ __forceinline__ void stsm_x4(uint32_t addr, uint32_t r0, uint32_t r1, uint32_t r2, uint32_t r3) {
    asm volatile("stmatrix.sync.aligned.m8n8.x4.shared.b16 [%0], {%1, %2, %3, %4};"
                 ::"r"(addr), "r"(r0), "r"(r1), "r"(r2), "r"(r3) : "memory");
}
__device__ __forceinline__ void wg_bar(int wg) { asm volatile("bar.sync %0, 128;" ::"r"(1 + wg) : "memory"); }
__device__ __forceinline__ void wgmma_fence() { asm volatile("wgmma.fence.sync.aligned;" ::: "memory"); }
__device__ __forceinline__ void wgmma_commit() { asm volatile("wgmma.commit_group.sync.aligned;" ::: "memory"); }
template <int N>
__device__ __forceinline__ void wgmma_wait() { asm volatile("wgmma.wait_group.sync.aligned %0;" ::"n"(N) : "memory"); }

__device__ __forceinline__ uint64_t make_desc(uint32_t addr, uint32_t lbo, uint32_t sbo, uint32_t swz = 1) {
    uint64_t d = 0;
    d |= (uint64_t)((addr & 0x3FFFF) >> 4);
    d |= (uint64_t)((lbo >> 4) & 0x3FFF) << 16;
    d |= (uint64_t)((sbo >> 4) & 0x3FFF) << 32;
    d |= (uint64_t)swz << 62;
    return d;
}

__device__ __forceinline__ void wgmma_m64n256k16(float (&d)[128], uint64_t da, uint64_t db, int scale_d) {
    asm volatile(
        "{\n"
        ".reg .pred p;\n"
        "setp.ne.b32 p, %130, 0;\n"
        "wgmma.mma_async.sync.aligned.m64n256k16.f32.bf16.bf16 "
        "{%0, %1, %2, %3, %4, %5, %6, %7, %8, %9, %10, %11, %12, %13, %14, %15, "
        "%16, %17, %18, %19, %20, %21, %22, %23, %24, %25, %26, %27, %28, %29, %30, %31, "
        "%32, %33, %34, %35, %36, %37, %38, %39, %40, %41, %42, %43, %44, %45, %46, %47, "
        "%48, %49, %50, %51, %52, %53, %54, %55, %56, %57, %58, %59, %60, %61, %62, %63, "
        "%64, %65, %66, %67, %68, %69, %70, %71, %72, %73, %74, %75, %76, %77, %78, %79, "
        "%80, %81, %82, %83, %84, %85, %86, %87, %88, %89, %90, %91, %92, %93, %94, %95, "
        "%96, %97, %98, %99, %100, %101, %102, %103, %104, %105, %106, %107, %108, %109, %110, %111, "
        "%112, %113, %114, %115, %116, %117, %118, %119, %120, %121, %122, %123, %124, %125, %126, %127}, "
        "%128, %129, p, 1, 1, 0, 1;\n"
        "}\n"
        : "+f"(d[0]), "+f"(d[1]), "+f"(d[2]), "+f"(d[3]), "+f"(d[4]), "+f"(d[5]), "+f"(d[6]), "+f"(d[7]),
          "+f"(d[8]), "+f"(d[9]), "+f"(d[10]), "+f"(d[11]), "+f"(d[12]), "+f"(d[13]), "+f"(d[14]), "+f"(d[15]),
          "+f"(d[16]), "+f"(d[17]), "+f"(d[18]), "+f"(d[19]), "+f"(d[20]), "+f"(d[21]), "+f"(d[22]), "+f"(d[23]),
          "+f"(d[24]), "+f"(d[25]), "+f"(d[26]), "+f"(d[27]), "+f"(d[28]), "+f"(d[29]), "+f"(d[30]), "+f"(d[31]),
          "+f"(d[32]), "+f"(d[33]), "+f"(d[34]), "+f"(d[35]), "+f"(d[36]), "+f"(d[37]), "+f"(d[38]), "+f"(d[39]),
          "+f"(d[40]), "+f"(d[41]), "+f"(d[42]), "+f"(d[43]), "+f"(d[44]), "+f"(d[45]), "+f"(d[46]), "+f"(d[47]),
          "+f"(d[48]), "+f"(d[49]), "+f"(d[50]), "+f"(d[51]), "+f"(d[52]), "+f"(d[53]), "+f"(d[54]), "+f"(d[55]),
          "+f"(d[56]), "+f"(d[57]), "+f"(d[58]), "+f"(d[59]), "+f"(d[60]), "+f"(d[61]), "+f"(d[62]), "+f"(d[63]),
          "+f"(d[64]), "+f"(d[65]), "+f"(d[66]), "+f"(d[67]), "+f"(d[68]), "+f"(d[69]), "+f"(d[70]), "+f"(d[71]),
          "+f"(d[72]), "+f"(d[73]), "+f"(d[74]), "+f"(d[75]), "+f"(d[76]), "+f"(d[77]), "+f"(d[78]), "+f"(d[79]),
          "+f"(d[80]), "+f"(d[81]), "+f"(d[82]), "+f"(d[83]), "+f"(d[84]), "+f"(d[85]), "+f"(d[86]), "+f"(d[87]),
          "+f"(d[88]), "+f"(d[89]), "+f"(d[90]), "+f"(d[91]), "+f"(d[92]), "+f"(d[93]), "+f"(d[94]), "+f"(d[95]),
          "+f"(d[96]), "+f"(d[97]), "+f"(d[98]), "+f"(d[99]), "+f"(d[100]), "+f"(d[101]), "+f"(d[102]), "+f"(d[103]),
          "+f"(d[104]), "+f"(d[105]), "+f"(d[106]), "+f"(d[107]), "+f"(d[108]), "+f"(d[109]), "+f"(d[110]), "+f"(d[111]),
          "+f"(d[112]), "+f"(d[113]), "+f"(d[114]), "+f"(d[115]), "+f"(d[116]), "+f"(d[117]), "+f"(d[118]), "+f"(d[119]),
          "+f"(d[120]), "+f"(d[121]), "+f"(d[122]), "+f"(d[123]), "+f"(d[124]), "+f"(d[125]), "+f"(d[126]), "+f"(d[127])
        : "l"(da), "l"(db), "r"(scale_d));
}

__device__ __forceinline__ void ldsm_x4(uint32_t addr, uint32_t& r0, uint32_t& r1, uint32_t& r2, uint32_t& r3) {
    asm volatile("ldmatrix.sync.aligned.m8n8.x4.shared.b16 {%0, %1, %2, %3}, [%4];"
                 : "=r"(r0), "=r"(r1), "=r"(r2), "=r"(r3) : "r"(addr));
}
__device__ __forceinline__ void ldsm_x4_t(uint32_t addr, uint32_t& r0, uint32_t& r1, uint32_t& r2, uint32_t& r3) {
    asm volatile("ldmatrix.sync.aligned.m8n8.x4.trans.shared.b16 {%0, %1, %2, %3}, [%4];"
                 : "=r"(r0), "=r"(r1), "=r"(r2), "=r"(r3) : "r"(addr));
}
__device__ __forceinline__ void mma_bf16(float (&c)[4], uint32_t a0, uint32_t a1, uint32_t a2, uint32_t a3,
                                         uint32_t b0, uint32_t b1) {
    asm volatile(
        "mma.sync.aligned.m16n8k16.row.col.f32.bf16.bf16.f32 {%0, %1, %2, %3}, {%4, %5, %6, %7}, {%8, %9}, "
        "{%0, %1, %2, %3};"
        : "+f"(c[0]), "+f"(c[1]), "+f"(c[2]), "+f"(c[3])
        : "r"(a0), "r"(a1), "r"(a2), "r"(a3), "r"(b0), "r"(b1));
}
__device__ __forceinline__ uint32_t pack_bf16(float lo, float hi) {
    __nv_bfloat162 v = __floats2bfloat162_rn(lo, hi);
    return *reinterpret_cast<uint32_t*>(&v);
}
__device__ __forceinline__ float bf16_round(float x) { return __bfloat162float(__float2bfloat16_rn(x)); }

template <int BK>
__device__ __forceinline__ void mainloop_consumer(float (&acc)[128], uint32_t smem_base, uint32_t full_bar,
                                                  uint32_t empty_bar, int wg, bool leader) {
    constexpr int KT = 1024 / BK;
    constexpr int STAGE = (BM + BN) * BK * 2;
    constexpr int ABYTES = BM * BK * 2;
#pragma unroll 1
    for (int it = 0; it < KT; ++it) {
        const int s = it % STAGES;
        mbar_wait(full_bar + 8 * s, (it / STAGES) & 1);
        const uint32_t a_addr = smem_base + s * STAGE + wg * (64 * BK * 2);
        const uint32_t b_addr = smem_base + s * STAGE + ABYTES;
        wgmma_fence();
#pragma unroll
        for (int k = 0; k < BK / 16; ++k) {
            uint64_t da = make_desc(a_addr + k * 32, 16, 8 * BK * 2, BK == 64 ? 1 : 2);
            uint64_t db = make_desc(b_addr + k * 2048, BK * 128, 1024);
            wgmma_m64n256k16(acc, da, db, (it | k) != 0);
        }
        wgmma_commit();
        if (it > 0) {
            wgmma_wait<1>();
            if (leader) {
                mbar_arrive_cluster(empty_bar + 8 * ((it - 1) % STAGES), 0);
                mbar_arrive_cluster(empty_bar + 8 * ((it - 1) % STAGES), 1);
            }
        }
    }
    wgmma_wait<0>();
}

template <int BK, bool PDL_WAIT, typename Hook>
__device__ __forceinline__ void mainloop_producer(uint32_t smem_base, uint32_t full_bar, uint32_t empty_bar,
                                                  const CUtensorMap* tmA, const CUtensorMap* tmB, int a_k0, int a_row,
                                                  int b_col, int b_k0, uint32_t crank, Hook hook) {
    constexpr int KT = 1024 / BK;
    constexpr int STAGE = (BM + BN) * BK * 2;
    constexpr int ABYTES = BM * BK * 2;
    for (int it = 0; it < KT; ++it) {
        const int s = it % STAGES;
        mbar_wait(empty_bar + 8 * s, ((it / STAGES) & 1) ^ 1);
        const uint32_t st = smem_base + s * STAGE;
        mbar_expect_tx(full_bar + 8 * s, STAGE);
#pragma unroll
        for (int jj = 0; jj < 2; ++jj) {
            const int j = crank * 2 + jj;
            tma_load_2d_mc(st + ABYTES + j * (BK * 128), tmB, full_bar + 8 * s, b_col + j * 64, b_k0 + it * BK,
                           (uint16_t)3);
        }
        if (PDL_WAIT && it == 0) asm volatile("griddepcontrol.wait;" ::: "memory");
        tma_load_2d(st, tmA, full_bar + 8 * s, a_k0 + it * BK, a_row);
        hook(it);
    }
}

__global__ void __cluster_dims__(2, 1, 1) __launch_bounds__(NTHREADS, 1)
qproj_attn_kernel(const __grid_constant__ CUtensorMap tmX0, const __grid_constant__ CUtensorMap tmX1,
                  const __grid_constant__ CUtensorMap tmW0, const __grid_constant__ CUtensorMap tmW1,
                  const __grid_constant__ CUtensorMap tmK0, const __grid_constant__ CUtensorMap tmK1,
                  const __grid_constant__ CUtensorMap tmV0, const __grid_constant__ CUtensorMap tmV1,
                  const __grid_constant__ CUtensorMap tmOst, const __nv_bfloat16* __restrict__ wo0,
                  const __nv_bfloat16* __restrict__ wo1) {
    extern __shared__ uint8_t smem_raw[];
    const uint32_t smem_base = (smem_u32(smem_raw) + 1023) & ~1023u;
    const uint32_t full_bar = smem_base + K1_BAR_OFF;
    const uint32_t empty_bar = full_bar + 8 * STAGES;
    const uint32_t kv_bar = empty_bar + 8 * STAGES;
    const uint32_t kv_base = smem_base + K1_KV_OFF;

    const int idx = blockIdx.x;
    const int blk = idx >> 6;
    const int nt = (idx & 63) >> 2;
    const int mt = idx & 3;
    const uint32_t crank = idx & 1;
    const int warp = threadIdx.x >> 5;
    const int lane = threadIdx.x & 31;

    if (threadIdx.x == 0) {
        for (int s = 0; s < STAGES; ++s) {
            mbar_init(full_bar + 8 * s, 1);
            mbar_init(empty_bar + 8 * s, 4);
        }
        mbar_init(kv_bar, 1);
        asm volatile("fence.mbarrier_init.release.cluster;" ::: "memory");
    }
    __syncthreads();
    STAMP(0, 0);
    cluster_sync_all();
    STAMP(0, 1);
    asm volatile("griddepcontrol.launch_dependents;" ::: "memory");

    if (warp >= 8) {
        if (warp == 8 && lane == 0) {
            const CUtensorMap* tmK = blk ? &tmK1 : &tmK0;
            const CUtensorMap* tmV = blk ? &tmV1 : &tmV0;
            mbar_expect_tx(kv_bar, 16 * BOX_BYTES);
            mainloop_producer<K1_BK, false>(
                smem_base, full_bar, empty_bar, blk ? &tmX1 : &tmX0, blk ? &tmW1 : &tmW0, 0, mt * BM, nt * BN, 0, crank,
                [&](int it) {
                    const int e = it - 3;
                    if (e >= 0 && e < 16) {
                        const int kv = e >> 3, bl = (e >> 1) & 3, half = e & 1;
                        const int row0 = ((mt * 4 + bl) * 32 + nt * 2) * 32;
                        tma_load_2d(kv_base + e * BOX_BYTES, kv ? tmV : tmK, kv_bar, half * 64, row0);
                    }
                });
            const char* wp = reinterpret_cast<const char*>(blk ? wo1 : wo0) + (size_t)(idx & 63) * 131072;
            for (int c = 0; c < 8; ++c)
                asm volatile("cp.async.bulk.prefetch.L2.global [%0], %1;" ::"l"(wp + c * 16384), "r"(16384) : "memory");
        }
    } else {
        const int wg = warp >> 2;
        const bool leader = (threadIdx.x & 127) == 0;
        float acc[128];
        mainloop_consumer<K1_BK>(acc, smem_base, full_bar, empty_bar, wg, leader);

        STAMP(0, 2);
        uint32_t qf[64];
#pragma unroll
        for (int i = 0; i < 64; ++i) qf[i] = pack_bf16(acc[2 * i], acc[2 * i + 1]);

        mbar_wait(kv_bar, 0);
        STAMP(0, 3);
        const int bl = wg * 2 + ((warp & 3) >> 1);
        const uint32_t kbase = kv_base + (bl * 2) * BOX_BYTES;
        const uint32_t vbase = kv_base + (8 + bl * 2) * BOX_BYTES;
        const int orow = wg * 64 + (warp & 3) * 16 + (lane & 7) + ((lane >> 3) & 1) * 8;
        const uint32_t ost = smem_base + orow * 128;

        float sc[2][4][4];
#pragma unroll
        for (int hh = 0; hh < 2; ++hh)
#pragma unroll
            for (int n = 0; n < 4; ++n)
#pragma unroll
                for (int c = 0; c < 4; ++c) sc[hh][n][c] = 0.f;
#pragma unroll
        for (int kk = 0; kk < 8; kk += 2) {
            const int chunk = 2 * kk + (lane >> 3);
            const int half = chunk >> 3, c8 = chunk & 7;
            uint32_t kb[2][4][4];
#pragma unroll
            for (int hh = 0; hh < 2; ++hh)
#pragma unroll
                for (int n = 0; n < 4; ++n) {
                    const int r = hh * 32 + n * 8 + (lane & 7);
                    ldsm_x4(kbase + half * BOX_BYTES + r * 128 + ((c8 ^ (r & 7)) << 4), kb[hh][n][0], kb[hh][n][1],
                            kb[hh][n][2], kb[hh][n][3]);
                }
#pragma unroll
            for (int u = 0; u < 2; ++u)
#pragma unroll
                for (int hh = 0; hh < 2; ++hh)
#pragma unroll
                    for (int n = 0; n < 4; ++n) {
                        const int q0 = hh * 32 + (kk + u) * 4;
                        mma_bf16(sc[hh][n], qf[q0 + 0], qf[q0 + 1], qf[q0 + 2], qf[q0 + 3], kb[hh][n][2 * u],
                                 kb[hh][n][2 * u + 1]);
                    }
        }
        uint32_t pf[2][2][4];
#pragma unroll
        for (int hh = 0; hh < 2; ++hh) {
            const float scale = 0.08838834764831845f;
            float m0 = -INFINITY, m1 = -INFINITY;
#pragma unroll
            for (int n = 0; n < 4; ++n) {
#pragma unroll
                for (int c = 0; c < 4; ++c) sc[hh][n][c] = bf16_round(bf16_round(sc[hh][n][c]) * scale);
                m0 = fmaxf(m0, fmaxf(sc[hh][n][0], sc[hh][n][1]));
                m1 = fmaxf(m1, fmaxf(sc[hh][n][2], sc[hh][n][3]));
            }
            m0 = fmaxf(m0, __shfl_xor_sync(0xffffffffu, m0, 1));
            m1 = fmaxf(m1, __shfl_xor_sync(0xffffffffu, m1, 1));
            m0 = fmaxf(m0, __shfl_xor_sync(0xffffffffu, m0, 2));
            m1 = fmaxf(m1, __shfl_xor_sync(0xffffffffu, m1, 2));
            float s0 = 0.f, s1 = 0.f;
#pragma unroll
            for (int n = 0; n < 4; ++n) {
                sc[hh][n][0] = __expf(sc[hh][n][0] - m0);
                sc[hh][n][1] = __expf(sc[hh][n][1] - m0);
                sc[hh][n][2] = __expf(sc[hh][n][2] - m1);
                sc[hh][n][3] = __expf(sc[hh][n][3] - m1);
                s0 += sc[hh][n][0] + sc[hh][n][1];
                s1 += sc[hh][n][2] + sc[hh][n][3];
            }
            s0 += __shfl_xor_sync(0xffffffffu, s0, 1);
            s1 += __shfl_xor_sync(0xffffffffu, s1, 1);
            s0 += __shfl_xor_sync(0xffffffffu, s0, 2);
            s1 += __shfl_xor_sync(0xffffffffu, s1, 2);
            const float i0 = 1.f / s0, i1 = 1.f / s1;
#pragma unroll
            for (int kk = 0; kk < 2; ++kk) {
                pf[hh][kk][0] = pack_bf16(sc[hh][2 * kk][0] * i0, sc[hh][2 * kk][1] * i0);
                pf[hh][kk][1] = pack_bf16(sc[hh][2 * kk][2] * i1, sc[hh][2 * kk][3] * i1);
                pf[hh][kk][2] = pack_bf16(sc[hh][2 * kk + 1][0] * i0, sc[hh][2 * kk + 1][1] * i0);
                pf[hh][kk][3] = pack_bf16(sc[hh][2 * kk + 1][2] * i1, sc[hh][2 * kk + 1][3] * i1);
            }
        }
        STAMP(0, 6);
#pragma unroll
        for (int hb = 0; hb < 4; ++hb) {
            const int hh = hb >> 1, half = hb & 1;
            const int r = hh * 32 + lane;
            const uint32_t addr = vbase + half * BOX_BYTES + r * 128;
            uint32_t vb[8][4];
#pragma unroll
            for (int c = 0; c < 8; ++c)
                ldsm_x4_t(addr + ((c ^ (r & 7)) << 4), vb[c][0], vb[c][1], vb[c][2], vb[c][3]);
            float oc[8][4];
#pragma unroll
            for (int c = 0; c < 8; ++c) {
                oc[c][0] = oc[c][1] = oc[c][2] = oc[c][3] = 0.f;
                mma_bf16(oc[c], pf[hh][0][0], pf[hh][0][1], pf[hh][0][2], pf[hh][0][3], vb[c][0], vb[c][1]);
            }
#pragma unroll
            for (int c = 0; c < 8; ++c)
                mma_bf16(oc[c], pf[hh][1][0], pf[hh][1][1], pf[hh][1][2], pf[hh][1][3], vb[c][2], vb[c][3]);
#pragma unroll
            for (int c = 0; c < 8; c += 2) {
                const int cn = c + (lane >> 4);
                stsm_x4(ost + hb * 16384 + ((cn ^ (orow & 7)) << 4), pack_bf16(oc[c][0], oc[c][1]),
                        pack_bf16(oc[c][2], oc[c][3]), pack_bf16(oc[c + 1][0], oc[c + 1][1]),
                        pack_bf16(oc[c + 1][2], oc[c + 1][3]));
            }
            if (hb == 1 || hb == 3) {
                fence_async_smem();
                wg_bar(wg);
                if (leader) {
                    tma_store_2d(&tmOst, smem_base + (hb - 1) * 16384 + wg * 8192, nt * 256 + (hb - 1) * 64,
                                 blk * 512 + mt * BM + wg * 64);
                    tma_store_2d(&tmOst, smem_base + hb * 16384 + wg * 8192, nt * 256 + hb * 64,
                                 blk * 512 + mt * BM + wg * 64);
                    asm volatile("cp.async.bulk.commit_group;" ::: "memory");
                }
            }
        }
        STAMP(0, 5);
        if (leader) asm volatile("cp.async.bulk.wait_group 0;" ::: "memory");
    }
    STAMP(0, 4);
    cluster_sync_all();
}

__device__ float4 g_red[32 * 4 * 4 * 8 * 256];

__global__ void __cluster_dims__(2, 1, 1) __launch_bounds__(NTHREADS, 1)
oproj_kernel(const __grid_constant__ CUtensorMap tmO, const __grid_constant__ CUtensorMap tmW0,
             const __grid_constant__ CUtensorMap tmW1, const __grid_constant__ CUtensorMap tmOut) {
    extern __shared__ uint8_t smem_raw[];
    const uint32_t smem_base = (smem_u32(smem_raw) + 1023) & ~1023u;
    const uint32_t full_bar = smem_base + K2_BAR_OFF;
    const uint32_t empty_bar = full_bar + 8 * STAGES;

    const int idx = blockIdx.x;
    const int blk = idx >> 6;
    const int ks = (idx >> 4) & 3;
    const int nt = (idx >> 2) & 3;
    const int mt = idx & 3;
    const uint32_t crank = idx & 1;
    const int tile = blk * 16 + mt * 4 + nt;
    const int warp = threadIdx.x >> 5;

    if (threadIdx.x == 0) {
        for (int s = 0; s < STAGES; ++s) {
            mbar_init(full_bar + 8 * s, 1);
            mbar_init(empty_bar + 8 * s, 4);
        }
        asm volatile("fence.mbarrier_init.release.cluster;" ::: "memory");
    }
    __syncthreads();
    STAMP(1, 0);
    cluster_sync_all();
    STAMP(1, 1);

    if (warp >= 8) {
        if (warp == 8 && (threadIdx.x & 31) == 0) {
            mainloop_producer<K2_BK, true>(smem_base, full_bar, empty_bar, &tmO, blk ? &tmW1 : &tmW0, ks * 1024,
                                           blk * 512 + mt * BM, nt * BN, ks * 1024, crank, [](int) {});
        }
    } else {
        const int wg = warp >> 2;
        const bool leader = (threadIdx.x & 127) == 0;
        float acc[128];
        mainloop_consumer<K2_BK>(acc, smem_base, full_bar, empty_bar, wg, leader);

        STAMP(1, 2);
        const int tid = threadIdx.x;
#pragma unroll
        for (int j = 0; j < 4; ++j) {
            if (j != ks) {
                float4* dst = g_red + ((size_t)((tile * 4 + j) * 4 + ks) * 8) * 256 + tid;
#pragma unroll
                for (int i = 0; i < 8; ++i) {
                    uint32_t w[4];
#pragma unroll
                    for (int c = 0; c < 4; ++c) {
                        w[c] = __float_as_uint(acc[j * 32 + i * 4 + c]);
                        if (w[c] == 0u) w[c] = 0x80000000u;
                    }
                    asm volatile("st.relaxed.gpu.global.v4.b32 [%0], {%1, %2, %3, %4};" ::"l"(dst + i * 256), "r"(w[0]),
                                 "r"(w[1]), "r"(w[2]), "r"(w[3]) : "memory");
                }
            }
        }
        STAMP(1, 5);
        const int lane = tid & 31;
        const int orow = wg * 64 + (warp & 3) * 16 + (lane & 7) + ((lane >> 3) & 1) * 8;
        const uint32_t ost = smem_base + orow * 128;
#pragma unroll
        for (int j = 0; j < 4; ++j) {
            if (j == ks) {
#pragma unroll
                for (int i = 0; i < 8; ++i) {
#pragma unroll
                    for (int sl = 0; sl < 4; ++sl) {
                        if (sl != j) {
                            float4* src = g_red + ((size_t)((tile * 4 + j) * 4 + sl) * 8 + i) * 256 + tid;
                            uint32_t w0, w1, w2, w3;
                            unsigned int spins = 0;
                            do {
                                asm volatile("ld.relaxed.gpu.global.v4.b32 {%0, %1, %2, %3}, [%4];"
                                             : "=r"(w0), "=r"(w1), "=r"(w2), "=r"(w3) : "l"(src) : "memory");
                            } while ((w0 == 0u || w1 == 0u || w2 == 0u || w3 == 0u) && ++spins < (1u << 22));
                            acc[j * 32 + i * 4 + 0] += __uint_as_float(w0);
                            acc[j * 32 + i * 4 + 1] += __uint_as_float(w1);
                            acc[j * 32 + i * 4 + 2] += __uint_as_float(w2);
                            acc[j * 32 + i * 4 + 3] += __uint_as_float(w3);
                            asm volatile("st.relaxed.gpu.global.v4.b32 [%0], {%1, %1, %1, %1};" ::"l"(src), "r"(0u)
                                         : "memory");
                        }
                    }
                }
                STAMP(1, 3);
#pragma unroll
                for (int i = 0; i < 8; i += 2) {
                    const int cn = i + (lane >> 4);
                    stsm_x4(ost + ((cn ^ (orow & 7)) << 4), pack_bf16(acc[j * 32 + i * 4 + 0], acc[j * 32 + i * 4 + 1]),
                            pack_bf16(acc[j * 32 + i * 4 + 2], acc[j * 32 + i * 4 + 3]),
                            pack_bf16(acc[j * 32 + i * 4 + 4], acc[j * 32 + i * 4 + 5]),
                            pack_bf16(acc[j * 32 + i * 4 + 6], acc[j * 32 + i * 4 + 7]));
                }
            }
        }
        fence_async_smem();
        wg_bar(wg);
        if (leader) {
            tma_store_2d(&tmOut, smem_base + wg * 8192, blk * 1024 + nt * 256 + ks * 64, mt * BM + wg * 64);
            tma_store_commit_wait();
        }
    }
    STAMP(1, 4);
    cluster_sync_all();
}

typedef CUresult (*EncodeFn)(CUtensorMap*, CUtensorMapDataType, cuuint32_t, void*, const cuuint64_t*,
                             const cuuint64_t*, const cuuint32_t*, const cuuint32_t*, CUtensorMapInterleave,
                             CUtensorMapSwizzle, CUtensorMapL2promotion, CUtensorMapFloatOOBfill);

EncodeFn get_encode() {
    static EncodeFn fn = nullptr;
    if (!fn) {
        void* p = nullptr;
        cudaDriverEntryPointQueryResult qres;
        cudaGetDriverEntryPoint("cuTensorMapEncodeTiled", &p, cudaEnableDefault, &qres);
        fn = (EncodeFn)p;
    }
    return fn;
}

CUtensorMap make_map(const void* ptr, uint64_t inner, uint64_t outer, uint32_t box_inner, uint32_t box_outer,
                     CUtensorMapSwizzle swz = CU_TENSOR_MAP_SWIZZLE_128B) {
    CUtensorMap m;
    cuuint64_t dims[2] = {inner, outer};
    cuuint64_t strides[1] = {inner * 2};
    cuuint32_t box[2] = {box_inner, box_outer};
    cuuint32_t estr[2] = {1, 1};
    get_encode()(&m, CU_TENSOR_MAP_DATA_TYPE_BFLOAT16, 2, const_cast<void*>(ptr), dims, strides, box, estr,
                 CU_TENSOR_MAP_INTERLEAVE_NONE, swz, CU_TENSOR_MAP_L2_PROMOTION_L2_256B,
                 CU_TENSOR_MAP_FLOAT_OOB_FILL_NONE);
    return m;
}

}

extern "C" void kernel_launch(void* const* d_in, const int* in_sizes, int n_in, void* d_out, int out_size) {
    (void)in_sizes; (void)n_in; (void)out_size;
    void* o_scratch = nullptr;
    cudaGetSymbolAddress(&o_scratch, g_o);

    CUtensorMap tmX[2], tmWq[2], tmK[2], tmV[2], tmWo[2];
    for (int b = 0; b < 2; ++b) {
        tmX[b] = make_map(d_in[b * 5 + 0], 1024, 512, K1_BK, 128, CU_TENSOR_MAP_SWIZZLE_64B);
        tmK[b] = make_map(d_in[b * 5 + 1], 128, 16384, 64, 64);
        tmV[b] = make_map(d_in[b * 5 + 2], 128, 16384, 64, 64);
        tmWq[b] = make_map(d_in[b * 5 + 3], 4096, 1024, 64, K1_BK);
        tmWo[b] = make_map(d_in[b * 5 + 4], 1024, 4096, 64, K2_BK);
    }
    CUtensorMap tmO = make_map(o_scratch, 4096, 1024, 64, 128);
    CUtensorMap tmOst = make_map(o_scratch, 4096, 1024, 64, 64);
    CUtensorMap tmOut = make_map(d_out, 2048, 512, 64, 64);

    static bool attr_done = false;
    if (!attr_done) {
        cudaFuncSetAttribute(qproj_attn_kernel, cudaFuncAttributeMaxDynamicSharedMemorySize, K1_SMEM);
        cudaFuncSetAttribute(oproj_kernel, cudaFuncAttributeMaxDynamicSharedMemorySize, K2_SMEM);
        attr_done = true;
    }
    qproj_attn_kernel<<<128, NTHREADS, K1_SMEM>>>(tmX[0], tmX[1], tmWq[0], tmWq[1], tmK[0], tmK[1], tmV[0], tmV[1],
                                                  tmOst, (const __nv_bfloat16*)d_in[4], (const __nv_bfloat16*)d_in[9]);
    cudaLaunchConfig_t cfg = {};
    cfg.gridDim = dim3(128);
    cfg.blockDim = dim3(NTHREADS);
    cfg.dynamicSmemBytes = K2_SMEM;
    cfg.stream = cudaStreamPerThread;
    cudaLaunchAttribute at[1];
    at[0].id = cudaLaunchAttributeProgrammaticStreamSerialization;
    at[0].val.programmaticStreamSerializationAllowed = 1;
    cfg.attrs = at;
    cfg.numAttrs = 1;
    cudaLaunchKernelEx(&cfg, oproj_kernel, tmO, tmWo[0], tmWo[1], tmOut);
}
```

```cpp
#include <cuda_runtime.h>
#include <cuda_bf16.h>
#include <cuda.h>
#include <stdint.h>

namespace {

constexpr int BM = 128, BN = 256, BK = 64;
constexpr int KT = 16;
constexpr int A_BYTES = BM * BK * 2;
constexpr int STAGE = (BM + BN) * BK * 2;
constexpr int BOX_BYTES = 64 * 64 * 2;
constexpr int NTHREADS = 384;
constexpr int K1_STAGES = 3;
constexpr int K1_K_OFF = K1_STAGES * STAGE;
constexpr int K1_BAR_OFF = K1_K_OFF + 8 * BOX_BYTES;
constexpr int K1_SMEM = K1_BAR_OFF + 128 + 1024;
constexpr int K2_STAGES = 4;
constexpr int K2_BAR_OFF = K2_STAGES * STAGE;
constexpr int K2_SMEM = K2_BAR_OFF + 128 + 1024;

__device__ __nv_bfloat16 g_o[2 * 512 * 4096];

#define STAMP(k, i) do { } while (0)

__device__ __forceinline__ uint32_t smem_u32(const void* p) {
    return (uint32_t)__cvta_generic_to_shared(p);
}
__device__ __forceinline__ void mbar_init(uint32_t bar, uint32_t count) {
    asm volatile("mbarrier.init.shared::cta.b64 [%0], %1;" ::"r"(bar), "r"(count));
}
__device__ __forceinline__ void mbar_expect_tx(uint32_t bar, uint32_t bytes) {
    asm volatile("mbarrier.arrive.expect_tx.shared::cta.b64 _, [%0], %1;" ::"r"(bar), "r"(bytes) : "memory");
}
__device__ __forceinline__ void mbar_arrive(uint32_t bar) {
    asm volatile("mbarrier.arrive.shared::cta.b64 _, [%0];" ::"r"(bar) : "memory");
}
__device__ __forceinline__ void mbar_wait(uint32_t bar, uint32_t parity) {
    asm volatile(
        "{\n"
        ".reg .pred P1;\n"
        "LAB_WAIT:\n"
        "mbarrier.try_wait.parity.shared::cta.b64 P1, [%0], %1;\n"
        "@P1 bra DONE;\n"
        "bra LAB_WAIT;\n"
        "DONE:\n"
        "}\n" ::"r"(bar), "r"(parity) : "memory");
}
__device__ __forceinline__ void tma_load_2d(uint32_t dst, const CUtensorMap* tm, uint32_t bar, int c0, int c1) {
    asm volatile(
        "cp.async.bulk.tensor.2d.shared::cluster.global.mbarrier::complete_tx::bytes [%0], [%1, {%3, %4}], [%2];"
        ::"r"(dst), "l"(tm), "r"(bar), "r"(c0), "r"(c1) : "memory");
}
__device__ __forceinline__ void tma_load_2d_mc(uint32_t dst, const CUtensorMap* tm, uint32_t bar, int c0, int c1,
                                               uint16_t mask) {
    asm volatile(
        "cp.async.bulk.tensor.2d.shared::cluster.global.mbarrier::complete_tx::bytes.multicast::cluster "
        "[%0], [%1, {%3, %4}], [%2], %5;"
        ::"r"(dst), "l"(tm), "r"(bar), "r"(c0), "r"(c1), "h"(mask) : "memory");
}
__device__ __forceinline__ void mbar_arrive_cluster(uint32_t bar, uint32_t rank) {
    asm volatile(
        "{\n"
        ".reg .b32 ra;\n"
        "mapa.shared::cluster.u32 ra, %0, %1;\n"
        "mbarrier.arrive.shared::cluster.b64 _, [ra];\n"
        "}\n" ::"r"(bar), "r"(rank) : "memory");
}
__device__ __forceinline__ void cluster_sync_all() {
    asm volatile("barrier.cluster.arrive.release.aligned;\nbarrier.cluster.wait.acquire.aligned;" ::: "memory");
}
__device__ __forceinline__ void tma_prefetch_2d(const CUtensorMap* tm, int c0, int c1) {
    asm volatile("cp.async.bulk.prefetch.tensor.2d.L2.global [%0, {%1, %2}];" ::"l"(tm), "r"(c0), "r"(c1) : "memory");
}
__device__ __forceinline__ void tma_store_2d(const CUtensorMap* tm, uint32_t src, int c0, int c1) {
    asm volatile("cp.async.bulk.tensor.2d.global.shared::cta.bulk_group [%0, {%2, %3}], [%1];"
                 ::"l"(tm), "r"(src), "r"(c0), "r"(c1) : "memory");
}
__device__ __forceinline__ void tma_store_commit_wait() {
    asm volatile("cp.async.bulk.commit_group;\ncp.async.bulk.wait_group 0;" ::: "memory");
}
__device__ __forceinline__ void fence_async_smem() { asm volatile("fence.proxy.async.shared::cta;" ::: "memory"); }
__device__ __forceinline__ void stsm_x4(uint32_t addr, uint32_t r0, uint32_t r1, uint32_t r2, uint32_t r3) {
    asm volatile("stmatrix.sync.aligned.m8n8.x4.shared.b16 [%0], {%1, %2, %3, %4};"
                 ::"r"(addr), "r"(r0), "r"(r1), "r"(r2), "r"(r3) : "memory");
}
__device__ __forceinline__ void wg_bar(int wg) { asm volatile("bar.sync %0, 128;" ::"r"(1 + wg) : "memory"); }
__device__ __forceinline__ void wgmma_fence() { asm volatile("wgmma.fence.sync.aligned;" ::: "memory"); }
__device__ __forceinline__ void wgmma_commit() { asm volatile("wgmma.commit_group.sync.aligned;" ::: "memory"); }
template <int N>
__device__ __forceinline__ void wgmma_wait() { asm volatile("wgmma.wait_group.sync.aligned %0;" ::"n"(N) : "memory"); }

__device__ __forceinline__ uint64_t make_desc(uint32_t addr, uint32_t lbo, uint32_t sbo, uint32_t swz = 1) {
    uint64_t d = 0;
    d |= (uint64_t)((addr & 0x3FFFF) >> 4);
    d |= (uint64_t)((lbo >> 4) & 0x3FFF) << 16;
    d |= (uint64_t)((sbo >> 4) & 0x3FFF) << 32;
    d |= (uint64_t)swz << 62;
    return d;
}

__device__ __forceinline__ void wgmma_m64n256k16(float (&d)[128], uint64_t da, uint64_t db, int scale_d) {
    asm volatile(
        "{\n"
        ".reg .pred p;\n"
        "setp.ne.b32 p, %130, 0;\n"
        "wgmma.mma_async.sync.aligned.m64n256k16.f32.bf16.bf16 "
        "{%0, %1, %2, %3, %4, %5, %6, %7, %8, %9, %10, %11, %12, %13, %14, %15, "
        "%16, %17, %18, %19, %20, %21, %22, %23, %24, %25, %26, %27, %28, %29, %30, %31, "
        "%32, %33, %34, %35, %36, %37, %38, %39, %40, %41, %42, %43, %44, %45, %46, %47, "
        "%48, %49, %50, %51, %52, %53, %54, %55, %56, %57, %58, %59, %60, %61, %62, %63, "
        "%64, %65, %66, %67, %68, %69, %70, %71, %72, %73, %74, %75, %76, %77, %78, %79, "
        "%80, %81, %82, %83, %84, %85, %86, %87, %88, %89, %90, %91, %92, %93, %94, %95, "
        "%96, %97, %98, %99, %100, %101, %102, %103, %104, %105, %106, %107, %108, %109, %110, %111, "
        "%112, %113, %114, %115, %116, %117, %118, %119, %120, %121, %122, %123, %124, %125, %126, %127}, "
        "%128, %129, p, 1, 1, 0, 1;\n"
        "}\n"
        : "+f"(d[0]), "+f"(d[1]), "+f"(d[2]), "+f"(d[3]), "+f"(d[4]), "+f"(d[5]), "+f"(d[6]), "+f"(d[7]),
          "+f"(d[8]), "+f"(d[9]), "+f"(d[10]), "+f"(d[11]), "+f"(d[12]), "+f"(d[13]), "+f"(d[14]), "+f"(d[15]),
          "+f"(d[16]), "+f"(d[17]), "+f"(d[18]), "+f"(d[19]), "+f"(d[20]), "+f"(d[21]), "+f"(d[22]), "+f"(d[23]),
          "+f"(d[24]), "+f"(d[25]), "+f"(d[26]), "+f"(d[27]), "+f"(d[28]), "+f"(d[29]), "+f"(d[30]), "+f"(d[31]),
          "+f"(d[32]), "+f"(d[33]), "+f"(d[34]), "+f"(d[35]), "+f"(d[36]), "+f"(d[37]), "+f"(d[38]), "+f"(d[39]),
          "+f"(d[40]), "+f"(d[41]), "+f"(d[42]), "+f"(d[43]), "+f"(d[44]), "+f"(d[45]), "+f"(d[46]), "+f"(d[47]),
          "+f"(d[48]), "+f"(d[49]), "+f"(d[50]), "+f"(d[51]), "+f"(d[52]), "+f"(d[53]), "+f"(d[54]), "+f"(d[55]),
          "+f"(d[56]), "+f"(d[57]), "+f"(d[58]), "+f"(d[59]), "+f"(d[60]), "+f"(d[61]), "+f"(d[62]), "+f"(d[63]),
          "+f"(d[64]), "+f"(d[65]), "+f"(d[66]), "+f"(d[67]), "+f"(d[68]), "+f"(d[69]), "+f"(d[70]), "+f"(d[71]),
          "+f"(d[72]), "+f"(d[73]), "+f"(d[74]), "+f"(d[75]), "+f"(d[76]), "+f"(d[77]), "+f"(d[78]), "+f"(d[79]),
          "+f"(d[80]), "+f"(d[81]), "+f"(d[82]), "+f"(d[83]), "+f"(d[84]), "+f"(d[85]), "+f"(d[86]), "+f"(d[87]),
          "+f"(d[88]), "+f"(d[89]), "+f"(d[90]), "+f"(d[91]), "+f"(d[92]), "+f"(d[93]), "+f"(d[94]), "+f"(d[95]),
          "+f"(d[96]), "+f"(d[97]), "+f"(d[98]), "+f"(d[99]), "+f"(d[100]), "+f"(d[101]), "+f"(d[102]), "+f"(d[103]),
          "+f"(d[104]), "+f"(d[105]), "+f"(d[106]), "+f"(d[107]), "+f"(d[108]), "+f"(d[109]), "+f"(d[110]), "+f"(d[111]),
          "+f"(d[112]), "+f"(d[113]), "+f"(d[114]), "+f"(d[115]), "+f"(d[116]), "+f"(d[117]), "+f"(d[118]), "+f"(d[119]),
          "+f"(d[120]), "+f"(d[121]), "+f"(d[122]), "+f"(d[123]), "+f"(d[124]), "+f"(d[125]), "+f"(d[126]), "+f"(d[127])
        : "l"(da), "l"(db), "r"(scale_d));
}

__device__ __forceinline__ void ldsm_x4(uint32_t addr, uint32_t& r0, uint32_t& r1, uint32_t& r2, uint32_t& r3) {
    asm volatile("ldmatrix.sync.aligned.m8n8.x4.shared.b16 {%0, %1, %2, %3}, [%4];"
                 : "=r"(r0), "=r"(r1), "=r"(r2), "=r"(r3) : "r"(addr));
}
__device__ __forceinline__ void ldsm_x4_t(uint32_t addr, uint32_t& r0, uint32_t& r1, uint32_t& r2, uint32_t& r3) {
    asm volatile("ldmatrix.sync.aligned.m8n8.x4.trans.shared.b16 {%0, %1, %2, %3}, [%4];"
                 : "=r"(r0), "=r"(r1), "=r"(r2), "=r"(r3) : "r"(addr));
}
__device__ __forceinline__ void mma_bf16(float (&c)[4], uint32_t a0, uint32_t a1, uint32_t a2, uint32_t a3,
                                         uint32_t b0, uint32_t b1) {
    asm volatile(
        "mma.sync.aligned.m16n8k16.row.col.f32.bf16.bf16.f32 {%0, %1, %2, %3}, {%4, %5, %6, %7}, {%8, %9}, "
        "{%0, %1, %2, %3};"
        : "+f"(c[0]), "+f"(c[1]), "+f"(c[2]), "+f"(c[3])
        : "r"(a0), "r"(a1), "r"(a2), "r"(a3), "r"(b0), "r"(b1));
}
__device__ __forceinline__ uint32_t pack_bf16(float lo, float hi) {
    __nv_bfloat162 v = __floats2bfloat162_rn(lo, hi);
    return *reinterpret_cast<uint32_t*>(&v);
}
__device__ __forceinline__ float bf16_round(float x) { return __bfloat162float(__float2bfloat16_rn(x)); }

template <int STAGES>
__device__ __forceinline__ void mainloop_consumer(float (&acc)[128], uint32_t smem_base, uint32_t full_bar,
                                                  uint32_t empty_bar, int wg, bool leader) {
#pragma unroll 1
    for (int it = 0; it < KT; ++it) {
        const int s = it % STAGES;
        mbar_wait(full_bar + 8 * s, (it / STAGES) & 1);
        const uint32_t a_addr = smem_base + s * STAGE + wg * (64 * BK * 2);
        const uint32_t b_addr = smem_base + s * STAGE + A_BYTES;
        wgmma_fence();
#pragma unroll
        for (int k = 0; k < BK / 16; ++k) {
            uint64_t da = make_desc(a_addr + k * 32, 16, 1024);
            uint64_t db = make_desc(b_addr + k * 2048, BOX_BYTES, 1024);
            wgmma_m64n256k16(acc, da, db, (it | k) != 0);
        }
        wgmma_commit();
        if (it > 0) {
            wgmma_wait<1>();
            if (leader) {
                mbar_arrive_cluster(empty_bar + 8 * ((it - 1) % STAGES), 0);
                mbar_arrive_cluster(empty_bar + 8 * ((it - 1) % STAGES), 1);
            }
        }
    }
    wgmma_wait<0>();
}

template <int STAGES, bool PDL_WAIT, typename Hook>
__device__ __forceinline__ void mainloop_producer(uint32_t smem_base, uint32_t full_bar, uint32_t empty_bar,
                                                  const CUtensorMap* tmA, const CUtensorMap* tmB, int a_k0, int a_row,
                                                  int b_col, int b_k0, uint32_t crank, Hook hook) {
    for (int it = 0; it < KT; ++it) {
        const int s = it % STAGES;
        mbar_wait(empty_bar + 8 * s, ((it / STAGES) & 1) ^ 1);
        const uint32_t st = smem_base + s * STAGE;
        mbar_expect_tx(full_bar + 8 * s, STAGE);
#pragma unroll
        for (int jj = 0; jj < 2; ++jj) {
            const int j = crank * 2 + jj;
            tma_load_2d_mc(st + A_BYTES + j * BOX_BYTES, tmB, full_bar + 8 * s, b_col + j * 64, b_k0 + it * BK,
                           (uint16_t)3);
        }
        if (PDL_WAIT && it == 0) asm volatile("griddepcontrol.wait;" ::: "memory");
        tma_load_2d(st, tmA, full_bar + 8 * s, a_k0 + it * BK, a_row);
        hook(it);
    }
}

__global__ void __cluster_dims__(2, 1, 1) __launch_bounds__(NTHREADS, 1)
qproj_attn_kernel(const __grid_constant__ CUtensorMap tmX0, const __grid_constant__ CUtensorMap tmX1,
                  const __grid_constant__ CUtensorMap tmW0, const __grid_constant__ CUtensorMap tmW1,
                  const __grid_constant__ CUtensorMap tmK0, const __grid_constant__ CUtensorMap tmK1,
                  const __grid_constant__ CUtensorMap tmV0, const __grid_constant__ CUtensorMap tmV1,
                  const __grid_constant__ CUtensorMap tmOst, const __nv_bfloat16* __restrict__ wo0,
                  const __nv_bfloat16* __restrict__ wo1) {
    extern __shared__ uint8_t smem_raw[];
    const uint32_t smem_base = (smem_u32(smem_raw) + 1023) & ~1023u;
    const uint32_t full_bar = smem_base + K1_BAR_OFF;
    const uint32_t empty_bar = full_bar + 8 * K1_STAGES;
    const uint32_t k_bar = empty_bar + 8 * K1_STAGES;
    const uint32_t k_base = smem_base + K1_K_OFF;

    const int idx = blockIdx.x;
    const int blk = idx >> 6;
    const int nt = (idx & 63) >> 2;
    const int mt = idx & 3;
    const uint32_t crank = idx & 1;
    const int warp = threadIdx.x >> 5;
    const int lane = threadIdx.x & 31;

    if (threadIdx.x == 0) {
        for (int s = 0; s < K1_STAGES; ++s) {
            mbar_init(full_bar + 8 * s, 1);
            mbar_init(empty_bar + 8 * s, 4);
        }
        mbar_init(k_bar, 1);
        asm volatile("fence.mbarrier_init.release.cluster;" ::: "memory");
    }
    __syncthreads();
    STAMP(0, 0);
    cluster_sync_all();
    STAMP(0, 1);
    asm volatile("griddepcontrol.launch_dependents;" ::: "memory");

    if (warp >= 8) {
        if (warp == 8 && lane == 0) {
            const CUtensorMap* tmK = blk ? &tmK1 : &tmK0;
            const CUtensorMap* tmV = blk ? &tmV1 : &tmV0;
            mbar_expect_tx(k_bar, 8 * BOX_BYTES);
            mainloop_producer<K1_STAGES, false>(
                smem_base, full_bar, empty_bar, blk ? &tmX1 : &tmX0, blk ? &tmW1 : &tmW0, 0, mt * BM, nt * BN, 0, crank,
                [&](int it) {
                    const int e = it - 2;
                    if (e >= 0 && e < 8)
                        tma_load_2d(k_base + e * BOX_BYTES, tmK, k_bar, (e & 1) * 64,
                                    ((mt * 4 + (e >> 1)) * 32 + nt * 2) * 32);
                });
            for (int t = 0; t < 2; ++t) {
                const int it = KT + t, s = it % K1_STAGES;
                mbar_wait(empty_bar + 8 * s, ((it / K1_STAGES) & 1) ^ 1);
                const int nbox = t ? 2 : 6;
                mbar_expect_tx(full_bar + 8 * s, nbox * BOX_BYTES);
                for (int j = 0; j < nbox; ++j) {
                    const int e = t * 6 + j;
                    tma_load_2d(smem_base + STAGE + e * BOX_BYTES, tmV, full_bar + 8 * s, (e & 1) * 64,
                                ((mt * 4 + (e >> 1)) * 32 + nt * 2) * 32);
                }
            }
            const char* wp = reinterpret_cast<const char*>(blk ? wo1 : wo0) + (size_t)(idx & 63) * 131072;
            for (int c = 0; c < 8; ++c)
                asm volatile("cp.async.bulk.prefetch.L2.global [%0], %1;" ::"l"(wp + c * 16384), "r"(16384) : "memory");
        }
    } else {
        const int wg = warp >> 2;
        const bool leader = (threadIdx.x & 127) == 0;
        float acc[128];
        mainloop_consumer<K1_STAGES>(acc, smem_base, full_bar, empty_bar, wg, leader);

        STAMP(0, 2);
        uint32_t qf[64];
#pragma unroll
        for (int i = 0; i < 64; ++i) qf[i] = pack_bf16(acc[2 * i], acc[2 * i + 1]);

        mbar_wait(k_bar, 0);
        asm volatile("bar.sync 3, 256;" ::: "memory");
        STAMP(0, 3);
        const int bl = wg * 2 + ((warp & 3) >> 1);
        const uint32_t kbase = k_base + (bl * 2) * BOX_BYTES;
        const uint32_t vbase = smem_base + STAGE + (bl * 2) * BOX_BYTES;
        const int orow = wg * 64 + (warp & 3) * 16 + (lane & 7) + ((lane >> 3) & 1) * 8;
        const uint32_t ost = smem_base + orow * 128;

        float sc[2][4][4];
#pragma unroll
        for (int hh = 0; hh < 2; ++hh)
#pragma unroll
            for (int n = 0; n < 4; ++n)
#pragma unroll
                for (int c = 0; c < 4; ++c) sc[hh][n][c] = 0.f;
#pragma unroll
        for (int kk = 0; kk < 8; kk += 2) {
            const int chunk = 2 * kk + (lane >> 3);
            const int half = chunk >> 3, c8 = chunk & 7;
            uint32_t kb[2][4][4];
#pragma unroll
            for (int hh = 0; hh < 2; ++hh)
#pragma unroll
                for (int n = 0; n < 4; ++n) {
                    const int r = hh * 32 + n * 8 + (lane & 7);
                    ldsm_x4(kbase + half * BOX_BYTES + r * 128 + ((c8 ^ (r & 7)) << 4), kb[hh][n][0], kb[hh][n][1],
                            kb[hh][n][2], kb[hh][n][3]);
                }
#pragma unroll
            for (int u = 0; u < 2; ++u)
#pragma unroll
                for (int hh = 0; hh < 2; ++hh)
#pragma unroll
                    for (int n = 0; n < 4; ++n) {
                        const int q0 = hh * 32 + (kk + u) * 4;
                        mma_bf16(sc[hh][n], qf[q0 + 0], qf[q0 + 1], qf[q0 + 2], qf[q0 + 3], kb[hh][n][2 * u],
                                 kb[hh][n][2 * u + 1]);
                    }
        }
        uint32_t pf[2][2][4];
#pragma unroll
        for (int hh = 0; hh < 2; ++hh) {
            const float scale = 0.08838834764831845f;
            float m0 = -INFINITY, m1 = -INFINITY;
#pragma unroll
            for (int n = 0; n < 4; ++n) {
#pragma unroll
                for (int c = 0; c < 4; ++c) sc[hh][n][c] = bf16_round(bf16_round(sc[hh][n][c]) * scale);
                m0 = fmaxf(m0, fmaxf(sc[hh][n][0], sc[hh][n][1]));
                m1 = fmaxf(m1, fmaxf(sc[hh][n][2], sc[hh][n][3]));
            }
            m0 = fmaxf(m0, __shfl_xor_sync(0xffffffffu, m0, 1));
            m1 = fmaxf(m1, __shfl_xor_sync(0xffffffffu, m1, 1));
            m0 = fmaxf(m0, __shfl_xor_sync(0xffffffffu, m0, 2));
            m1 = fmaxf(m1, __shfl_xor_sync(0xffffffffu, m1, 2));
            float s0 = 0.f, s1 = 0.f;
#pragma unroll
            for (int n = 0; n < 4; ++n) {
                sc[hh][n][0] = __expf(sc[hh][n][0] - m0);
                sc[hh][n][1] = __expf(sc[hh][n][1] - m0);
                sc[hh][n][2] = __expf(sc[hh][n][2] - m1);
                sc[hh][n][3] = __expf(sc[hh][n][3] - m1);
                s0 += sc[hh][n][0] + sc[hh][n][1];
                s1 += sc[hh][n][2] + sc[hh][n][3];
            }
            s0 += __shfl_xor_sync(0xffffffffu, s0, 1);
            s1 += __shfl_xor_sync(0xffffffffu, s1, 1);
            s0 += __shfl_xor_sync(0xffffffffu, s0, 2);
            s1 += __shfl_xor_sync(0xffffffffu, s1, 2);
            const float i0 = 1.f / s0, i1 = 1.f / s1;
#pragma unroll
            for (int kk = 0; kk < 2; ++kk) {
                pf[hh][kk][0] = pack_bf16(sc[hh][2 * kk][0] * i0, sc[hh][2 * kk][1] * i0);
                pf[hh][kk][1] = pack_bf16(sc[hh][2 * kk][2] * i1, sc[hh][2 * kk][3] * i1);
                pf[hh][kk][2] = pack_bf16(sc[hh][2 * kk + 1][0] * i0, sc[hh][2 * kk + 1][1] * i0);
                pf[hh][kk][3] = pack_bf16(sc[hh][2 * kk + 1][2] * i1, sc[hh][2 * kk + 1][3] * i1);
            }
        }
        STAMP(0, 6);
        mbar_wait(full_bar + 8 * (KT % K1_STAGES), (KT / K1_STAGES) & 1);
        mbar_wait(full_bar + 8 * ((KT + 1) % K1_STAGES), ((KT + 1) / K1_STAGES) & 1);
#pragma unroll
        for (int hb = 0; hb < 4; ++hb) {
            const int hh = hb >> 1, half = hb & 1;
            const int r = hh * 32 + lane;
            const uint32_t addr = vbase + half * BOX_BYTES + r * 128;
            uint32_t vb[8][4];
#pragma unroll
            for (int c = 0; c < 8; ++c)
                ldsm_x4_t(addr + ((c ^ (r & 7)) << 4), vb[c][0], vb[c][1], vb[c][2], vb[c][3]);
            float oc[8][4];
#pragma unroll
            for (int c = 0; c < 8; ++c) {
                oc[c][0] = oc[c][1] = oc[c][2] = oc[c][3] = 0.f;
                mma_bf16(oc[c], pf[hh][0][0], pf[hh][0][1], pf[hh][0][2], pf[hh][0][3], vb[c][0], vb[c][1]);
            }
#pragma unroll
            for (int c = 0; c < 8; ++c)
                mma_bf16(oc[c], pf[hh][1][0], pf[hh][1][1], pf[hh][1][2], pf[hh][1][3], vb[c][2], vb[c][3]);
#pragma unroll
            for (int c = 0; c < 8; c += 2) {
                const int cn = c + (lane >> 4);
                stsm_x4(ost + (hb == 3 ? 7 : hb) * 16384 + ((cn ^ (orow & 7)) << 4), pack_bf16(oc[c][0], oc[c][1]),
                        pack_bf16(oc[c][2], oc[c][3]), pack_bf16(oc[c + 1][0], oc[c + 1][1]),
                        pack_bf16(oc[c + 1][2], oc[c + 1][3]));
            }
            if (hb == 1 || hb == 3) {
                fence_async_smem();
                wg_bar(wg);
                if (leader) {
                    tma_store_2d(&tmOst, smem_base + (hb - 1) * 16384 + wg * 8192, nt * 256 + (hb - 1) * 64,
                                 blk * 512 + mt * BM + wg * 64);
                    tma_store_2d(&tmOst, smem_base + (hb == 3 ? 7 : hb) * 16384 + wg * 8192, nt * 256 + hb * 64,
                                 blk * 512 + mt * BM + wg * 64);
                    asm volatile("cp.async.bulk.commit_group;" ::: "memory");
                }
            }
        }
        STAMP(0, 5);
        if (leader) asm volatile("cp.async.bulk.wait_group 0;" ::: "memory");
    }
    STAMP(0, 4);
    cluster_sync_all();
}

__device__ float4 g_red[32 * 4 * 4 * 8 * 256];
__device__ unsigned int g_flag[32 * 4 * 8];

__global__ void __cluster_dims__(2, 1, 1) __launch_bounds__(NTHREADS, 1)
oproj_kernel(const __grid_constant__ CUtensorMap tmO, const __grid_constant__ CUtensorMap tmW0,
             const __grid_constant__ CUtensorMap tmW1, const __grid_constant__ CUtensorMap tmOut) {
    extern __shared__ uint8_t smem_raw[];
    const uint32_t smem_base = (smem_u32(smem_raw) + 1023) & ~1023u;
    const uint32_t full_bar = smem_base + K2_BAR_OFF;
    const uint32_t empty_bar = full_bar + 8 * K2_STAGES;

    const int idx = blockIdx.x;
    const int blk = idx >> 6;
    const int ks = (idx >> 4) & 3;
    const int nt = (idx >> 2) & 3;
    const int mt = idx & 3;
    const uint32_t crank = idx & 1;
    const int tile = blk * 16 + mt * 4 + nt;
    const int warp = threadIdx.x >> 5;

    if (threadIdx.x == 0) {
        for (int s = 0; s < K2_STAGES; ++s) {
            mbar_init(full_bar + 8 * s, 1);
            mbar_init(empty_bar + 8 * s, 4);
        }
        asm volatile("fence.mbarrier_init.release.cluster;" ::: "memory");
    }
    __syncthreads();
    STAMP(1, 0);
    cluster_sync_all();
    STAMP(1, 1);

    if (warp >= 8) {
        if (warp == 8 && (threadIdx.x & 31) == 0) {
            mainloop_producer<K2_STAGES, true>(smem_base, full_bar, empty_bar, &tmO, blk ? &tmW1 : &tmW0, ks * 1024,
                                           blk * 512 + mt * BM, nt * BN, ks * 1024, crank, [](int) {});
        }
    } else {
        const int wg = warp >> 2;
        const bool leader = (threadIdx.x & 127) == 0;
        float acc[128];
        mainloop_consumer<K2_STAGES>(acc, smem_base, full_bar, empty_bar, wg, leader);

        STAMP(1, 2);
        const int tid = threadIdx.x;
#pragma unroll
        for (int j = 0; j < 4; ++j) {
            if (j != ks) {
                float4* dst = g_red + ((size_t)((tile * 4 + j) * 4 + ks) * 8) * 256 + tid;
#pragma unroll
                for (int i = 0; i < 8; ++i)
                    __stcg(dst + i * 256, make_float4(acc[j * 32 + i * 4 + 0], acc[j * 32 + i * 4 + 1],
                                                      acc[j * 32 + i * 4 + 2], acc[j * 32 + i * 4 + 3]));
            }
        }
        STAMP(1, 5);
        __threadfence();
        __syncwarp();
        STAMP(1, 6);
        if ((tid & 31) == 0) {
#pragma unroll
            for (int j = 0; j < 4; ++j)
                if (j != ks) atomicAdd(&g_flag[(tile * 4 + j) * 8 + warp], 1u);
            volatile unsigned int* f = &g_flag[(tile * 4 + ks) * 8 + warp];
            unsigned int spins = 0;
            while (*f < 3u && ++spins < (1u << 26)) { }
            *f = 0;
            __threadfence();
        }
        __syncwarp();
        STAMP(1, 3);
        const int lane = tid & 31;
        const int orow = wg * 64 + (warp & 3) * 16 + (lane & 7) + ((lane >> 3) & 1) * 8;
        const uint32_t ost = smem_base + orow * 128;
#pragma unroll
        for (int j = 0; j < 4; ++j) {
            if (j == ks) {
#pragma unroll
                for (int i = 0; i < 8; i += 2) {
                    uint32_t pk[4];
#pragma unroll
                    for (int u = 0; u < 2; ++u) {
                        float v0 = acc[j * 32 + (i + u) * 4 + 0], v1 = acc[j * 32 + (i + u) * 4 + 1];
                        float v2 = acc[j * 32 + (i + u) * 4 + 2], v3 = acc[j * 32 + (i + u) * 4 + 3];
#pragma unroll
                        for (int sl = 0; sl < 4; ++sl) {
                            if (sl != j) {
                                float4 r = __ldcg(g_red + ((size_t)((tile * 4 + j) * 4 + sl) * 8 + i + u) * 256 + tid);
                                v0 += r.x; v1 += r.y; v2 += r.z; v3 += r.w;
                            }
                        }
                        pk[u * 2 + 0] = pack_bf16(v0, v1);
                        pk[u * 2 + 1] = pack_bf16(v2, v3);
                    }
                    const int cn = i + (lane >> 4);
                    stsm_x4(ost + ((cn ^ (orow & 7)) << 4), pk[0], pk[1], pk[2], pk[3]);
                }
            }
        }
        fence_async_smem();
        wg_bar(wg);
        if (leader) {
            tma_store_2d(&tmOut, smem_base + wg * 8192, blk * 1024 + nt * 256 + ks * 64, mt * BM + wg * 64);
            tma_store_commit_wait();
        }
    }
    STAMP(1, 4);
    cluster_sync_all();
}

typedef CUresult (*EncodeFn)(CUtensorMap*, CUtensorMapDataType, cuuint32_t, void*, const cuuint64_t*,
                             const cuuint64_t*, const cuuint32_t*, const cuuint32_t*, CUtensorMapInterleave,
                             CUtensorMapSwizzle, CUtensorMapL2promotion, CUtensorMapFloatOOBfill);

EncodeFn get_encode() {
    static EncodeFn fn = nullptr;
    if (!fn) {
        void* p = nullptr;
        cudaDriverEntryPointQueryResult qres;
        cudaGetDriverEntryPoint("cuTensorMapEncodeTiled", &p, cudaEnableDefault, &qres);
        fn = (EncodeFn)p;
    }
    return fn;
}

CUtensorMap make_map(const void* ptr, uint64_t inner, uint64_t outer, uint32_t box_inner, uint32_t box_outer,
                     CUtensorMapSwizzle swz = CU_TENSOR_MAP_SWIZZLE_128B) {
    CUtensorMap m;
    cuuint64_t dims[2] = {inner, outer};
    cuuint64_t strides[1] = {inner * 2};
    cuuint32_t box[2] = {box_inner, box_outer};
    cuuint32_t estr[2] = {1, 1};
    get_encode()(&m, CU_TENSOR_MAP_DATA_TYPE_BFLOAT16, 2, const_cast<void*>(ptr), dims, strides, box, estr,
                 CU_TENSOR_MAP_INTERLEAVE_NONE, swz, CU_TENSOR_MAP_L2_PROMOTION_L2_256B,
                 CU_TENSOR_MAP_FLOAT_OOB_FILL_NONE);
    return m;
}

}

extern "C" void kernel_launch(void* const* d_in, const int* in_sizes, int n_in, void* d_out, int out_size) {
    (void)in_sizes; (void)n_in; (void)out_size;
    void* o_scratch = nullptr;
    cudaGetSymbolAddress(&o_scratch, g_o);

    CUtensorMap tmX[2], tmWq[2], tmK[2], tmV[2], tmWo[2];
    for (int b = 0; b < 2; ++b) {
        tmX[b] = make_map(d_in[b * 5 + 0], 1024, 512, 64, 128);
        tmK[b] = make_map(d_in[b * 5 + 1], 128, 16384, 64, 64);
        tmV[b] = make_map(d_in[b * 5 + 2], 128, 16384, 64, 64);
        tmWq[b] = make_map(d_in[b * 5 + 3], 4096, 1024, 64, 64);
        tmWo[b] = make_map(d_in[b * 5 + 4], 1024, 4096, 64, 64);
    }
    CUtensorMap tmO = make_map(o_scratch, 4096, 1024, 64, 128);
    CUtensorMap tmOst = make_map(o_scratch, 4096, 1024, 64, 64);
    CUtensorMap tmOut = make_map(d_out, 2048, 512, 64, 64);

    static bool attr_done = false;
    if (!attr_done) {
        cudaFuncSetAttribute(qproj_attn_kernel, cudaFuncAttributeMaxDynamicSharedMemorySize, K1_SMEM);
        cudaFuncSetAttribute(oproj_kernel, cudaFuncAttributeMaxDynamicSharedMemorySize, K2_SMEM);
        attr_done = true;
    }
    qproj_attn_kernel<<<128, NTHREADS, K1_SMEM>>>(tmX[0], tmX[1], tmWq[0], tmWq[1], tmK[0], tmK[1], tmV[0], tmV[1],
                                                  tmOst, (const __nv_bfloat16*)d_in[4], (const __nv_bfloat16*)d_in[9]);
    cudaLaunchConfig_t cfg = {};
    cfg.gridDim = dim3(128);
    cfg.blockDim = dim3(NTHREADS);
    cfg.dynamicSmemBytes = K2_SMEM;
    cfg.stream = cudaStreamPerThread;
    cudaLaunchAttribute at[1];
    at[0].id = cudaLaunchAttributeProgrammaticStreamSerialization;
    at[0].val.programmaticStreamSerializationAllowed = 1;
    cfg.attrs = at;
    cfg.numAttrs = 1;
    cudaLaunchKernelEx(&cfg, oproj_kernel, tmO, tmWo[0], tmWo[1], tmOut);
}
```

```cpp
#include <cuda_runtime.h>
#include <cuda_bf16.h>
#include <cuda.h>
#include <stdint.h>

namespace {

constexpr int BM = 128, BN = 256, BK = 64;
constexpr int KT = 16;
constexpr int A_BYTES = BM * BK * 2;
constexpr int STAGE = (BM + BN) * BK * 2;
constexpr int BOX_BYTES = 64 * 64 * 2;
constexpr int NTHREADS = 384;
constexpr int K1_STAGES = 3;
constexpr int K1_K_OFF = K1_STAGES * STAGE;
constexpr int K1_BAR_OFF = K1_K_OFF + 8 * BOX_BYTES;
constexpr int K1_SMEM = K1_BAR_OFF + 128 + 1024;
constexpr int K2_STAGES = 4;
constexpr int K2_BAR_OFF = K2_STAGES * STAGE;
constexpr int K2_SMEM = K2_BAR_OFF + 128 + 1024;

__device__ __nv_bfloat16 g_o[2 * 512 * 4096];

#define STAMP(k, i) do { } while (0)

__device__ __forceinline__ uint32_t smem_u32(const void* p) {
    return (uint32_t)__cvta_generic_to_shared(p);
}
__device__ __forceinline__ void mbar_init(uint32_t bar, uint32_t count) {
    asm volatile("mbarrier.init.shared::cta.b64 [%0], %1;" ::"r"(bar), "r"(count));
}
__device__ __forceinline__ void mbar_expect_tx(uint32_t bar, uint32_t bytes) {
    asm volatile("mbarrier.arrive.expect_tx.shared::cta.b64 _, [%0], %1;" ::"r"(bar), "r"(bytes) : "memory");
}
__device__ __forceinline__ void mbar_arrive(uint32_t bar) {
    asm volatile("mbarrier.arrive.shared::cta.b64 _, [%0];" ::"r"(bar) : "memory");
}
__device__ __forceinline__ void mbar_wait(uint32_t bar, uint32_t parity) {
    asm volatile(
        "{\n"
        ".reg .pred P1;\n"
        "LAB_WAIT:\n"
        "mbarrier.try_wait.parity.shared::cta.b64 P1, [%0], %1;\n"
        "@P1 bra DONE;\n"
        "bra LAB_WAIT;\n"
        "DONE:\n"
        "}\n" ::"r"(bar), "r"(parity) : "memory");
}
__device__ __forceinline__ void tma_load_2d(uint32_t dst, const CUtensorMap* tm, uint32_t bar, int c0, int c1) {
    asm volatile(
        "cp.async.bulk.tensor.2d.shared::cluster.global.mbarrier::complete_tx::bytes [%0], [%1, {%3, %4}], [%2];"
        ::"r"(dst), "l"(tm), "r"(bar), "r"(c0), "r"(c1) : "memory");
}
__device__ __forceinline__ void tma_load_2d_mc(uint32_t dst, const CUtensorMap* tm, uint32_t bar, int c0, int c1,
                                               uint16_t mask) {
    asm volatile(
        "cp.async.bulk.tensor.2d.shared::cluster.global.mbarrier::complete_tx::bytes.multicast::cluster "
        "[%0], [%1, {%3, %4}], [%2], %5;"
        ::"r"(dst), "l"(tm), "r"(bar), "r"(c0), "r"(c1), "h"(mask) : "memory");
}
__device__ __forceinline__ void mbar_arrive_cluster(uint32_t bar, uint32_t rank) {
    asm volatile(
        "{\n"
        ".reg .b32 ra;\n"
        "mapa.shared::cluster.u32 ra, %0, %1;\n"
        "mbarrier.arrive.shared::cluster.b64 _, [ra];\n"
        "}\n" ::"r"(bar), "r"(rank) : "memory");
}
__device__ __forceinline__ void cluster_sync_all() {
    asm volatile("barrier.cluster.arrive.release.aligned;\nbarrier.cluster.wait.acquire.aligned;" ::: "memory");
}
__device__ __forceinline__ void tma_store_2d(const CUtensorMap* tm, uint32_t src, int c0, int c1) {
    asm volatile("cp.async.bulk.tensor.2d.global.shared::cta.bulk_group [%0, {%2, %3}], [%1];"
                 ::"l"(tm), "r"(src), "r"(c0), "r"(c1) : "memory");
}
__device__ __forceinline__ void tma_store_commit_wait() {
    asm volatile("cp.async.bulk.commit_group;\ncp.async.bulk.wait_group 0;" ::: "memory");
}
__device__ __forceinline__ void fence_async_smem() { asm volatile("fence.proxy.async.shared::cta;" ::: "memory"); }
__device__ __forceinline__ void stsm_x4(uint32_t addr, uint32_t r0, uint32_t r1, uint32_t r2, uint32_t r3) {
    asm volatile("stmatrix.sync.aligned.m8n8.x4.shared.b16 [%0], {%1, %2, %3, %4};"
                 ::"r"(addr), "r"(r0), "r"(r1), "r"(r2), "r"(r3) : "memory");
}
__device__ __forceinline__ void wg_bar(int wg) { asm volatile("bar.sync %0, 128;" ::"r"(1 + wg) : "memory"); }
__device__ __forceinline__ void wgmma_fence() { asm volatile("wgmma.fence.sync.aligned;" ::: "memory"); }
__device__ __forceinline__ void wgmma_commit() { asm volatile("wgmma.commit_group.sync.aligned;" ::: "memory"); }
template <int N>
__device__ __forceinline__ void wgmma_wait() { asm volatile("wgmma.wait_group.sync.aligned %0;" ::"n"(N) : "memory"); }

__device__ __forceinline__ uint64_t make_desc(uint32_t addr, uint32_t lbo, uint32_t sbo, uint32_t swz = 1) {
    uint64_t d = 0;
    d |= (uint64_t)((addr & 0x3FFFF) >> 4);
    d |= (uint64_t)((lbo >> 4) & 0x3FFF) << 16;
    d |= (uint64_t)((sbo >> 4) & 0x3FFF) << 32;
    d |= (uint64_t)swz << 62;
    return d;
}

__device__ __forceinline__ void wgmma_m64n256k16(float (&d)[128], uint64_t da, uint64_t db, int scale_d) {
    asm volatile(
        "{\n"
        ".reg .pred p;\n"
        "setp.ne.b32 p, %130, 0;\n"
        "wgmma.mma_async.sync.aligned.m64n256k16.f32.bf16.bf16 "
        "{%0, %1, %2, %3, %4, %5, %6, %7, %8, %9, %10, %11, %12, %13, %14, %15, "
        "%16, %17, %18, %19, %20, %21, %22, %23, %24, %25, %26, %27, %28, %29, %30, %31, "
        "%32, %33, %34, %35, %36, %37, %38, %39, %40, %41, %42, %43, %44, %45, %46, %47, "
        "%48, %49, %50, %51, %52, %53, %54, %55, %56, %57, %58, %59, %60, %61, %62, %63, "
        "%64, %65, %66, %67, %68, %69, %70, %71, %72, %73, %74, %75, %76, %77, %78, %79, "
        "%80, %81, %82, %83, %84, %85, %86, %87, %88, %89, %90, %91, %92, %93, %94, %95, "
        "%96, %97, %98, %99, %100, %101, %102, %103, %104, %105, %106, %107, %108, %109, %110, %111, "
        "%112, %113, %114, %115, %116, %117, %118, %119, %120, %121, %122, %123, %124, %125, %126, %127}, "
        "%128, %129, p, 1, 1, 0, 1;\n"
        "}\n"
        : "+f"(d[0]), "+f"(d[1]), "+f"(d[2]), "+f"(d[3]), "+f"(d[4]), "+f"(d[5]), "+f"(d[6]), "+f"(d[7]),
          "+f"(d[8]), "+f"(d[9]), "+f"(d[10]), "+f"(d[11]), "+f"(d[12]), "+f"(d[13]), "+f"(d[14]), "+f"(d[15]),
          "+f"(d[16]), "+f"(d[17]), "+f"(d[18]), "+f"(d[19]), "+f"(d[20]), "+f"(d[21]), "+f"(d[22]), "+f"(d[23]),
          "+f"(d[24]), "+f"(d[25]), "+f"(d[26]), "+f"(d[27]), "+f"(d[28]), "+f"(d[29]), "+f"(d[30]), "+f"(d[31]),
          "+f"(d[32]), "+f"(d[33]), "+f"(d[34]), "+f"(d[35]), "+f"(d[36]), "+f"(d[37]), "+f"(d[38]), "+f"(d[39]),
          "+f"(d[40]), "+f"(d[41]), "+f"(d[42]), "+f"(d[43]), "+f"(d[44]), "+f"(d[45]), "+f"(d[46]), "+f"(d[47]),
          "+f"(d[48]), "+f"(d[49]), "+f"(d[50]), "+f"(d[51]), "+f"(d[52]), "+f"(d[53]), "+f"(d[54]), "+f"(d[55]),
          "+f"(d[56]), "+f"(d[57]), "+f"(d[58]), "+f"(d[59]), "+f"(d[60]), "+f"(d[61]), "+f"(d[62]), "+f"(d[63]),
          "+f"(d[64]), "+f"(d[65]), "+f"(d[66]), "+f"(d[67]), "+f"(d[68]), "+f"(d[69]), "+f"(d[70]), "+f"(d[71]),
          "+f"(d[72]), "+f"(d[73]), "+f"(d[74]), "+f"(d[75]), "+f"(d[76]), "+f"(d[77]), "+f"(d[78]), "+f"(d[79]),
          "+f"(d[80]), "+f"(d[81]), "+f"(d[82]), "+f"(d[83]), "+f"(d[84]), "+f"(d[85]), "+f"(d[86]), "+f"(d[87]),
          "+f"(d[88]), "+f"(d[89]), "+f"(d[90]), "+f"(d[91]), "+f"(d[92]), "+f"(d[93]), "+f"(d[94]), "+f"(d[95]),
          "+f"(d[96]), "+f"(d[97]), "+f"(d[98]), "+f"(d[99]), "+f"(d[100]), "+f"(d[101]), "+f"(d[102]), "+f"(d[103]),
          "+f"(d[104]), "+f"(d[105]), "+f"(d[106]), "+f"(d[107]), "+f"(d[108]), "+f"(d[109]), "+f"(d[110]), "+f"(d[111]),
          "+f"(d[112]), "+f"(d[113]), "+f"(d[114]), "+f"(d[115]), "+f"(d[116]), "+f"(d[117]), "+f"(d[118]), "+f"(d[119]),
          "+f"(d[120]), "+f"(d[121]), "+f"(d[122]), "+f"(d[123]), "+f"(d[124]), "+f"(d[125]), "+f"(d[126]), "+f"(d[127])
        : "l"(da), "l"(db), "r"(scale_d));
}

__device__ __forceinline__ void ldsm_x4(uint32_t addr, uint32_t& r0, uint32_t& r1, uint32_t& r2, uint32_t& r3) {
    asm volatile("ldmatrix.sync.aligned.m8n8.x4.shared.b16 {%0, %1, %2, %3}, [%4];"
                 : "=r"(r0), "=r"(r1), "=r"(r2), "=r"(r3) : "r"(addr));
}
__device__ __forceinline__ void ldsm_x4_t(uint32_t addr, uint32_t& r0, uint32_t& r1, uint32_t& r2, uint32_t& r3) {
    asm volatile("ldmatrix.sync.aligned.m8n8.x4.trans.shared.b16 {%0, %1, %2, %3}, [%4];"
                 : "=r"(r0), "=r"(r1), "=r"(r2), "=r"(r3) : "r"(addr));
}
__device__ __forceinline__ void mma_bf16(float (&c)[4], uint32_t a0, uint32_t a1, uint32_t a2, uint32_t a3,
                                         uint32_t b0, uint32_t b1) {
    asm volatile(
        "mma.sync.aligned.m16n8k16.row.col.f32.bf16.bf16.f32 {%0, %1, %2, %3}, {%4, %5, %6, %7}, {%8, %9}, "
        "{%0, %1, %2, %3};"
        : "+f"(c[0]), "+f"(c[1]), "+f"(c[2]), "+f"(c[3])
        : "r"(a0), "r"(a1), "r"(a2), "r"(a3), "r"(b0), "r"(b1));
}
__device__ __forceinline__ uint32_t pack_bf16(float lo, float hi) {
    __nv_bfloat162 v = __floats2bfloat162_rn(lo, hi);
    return *reinterpret_cast<uint32_t*>(&v);
}
__device__ __forceinline__ float bf16_round(float x) { return __bfloat162float(__float2bfloat16_rn(x)); }

template <int STAGES>
__device__ __forceinline__ void mainloop_consumer(float (&acc)[128], uint32_t smem_base, uint32_t full_bar,
                                                  uint32_t empty_bar, int wg, bool leader) {
#pragma unroll 1
    for (int it = 0; it < KT; ++it) {
        const int s = it % STAGES;
        mbar_wait(full_bar + 8 * s, (it / STAGES) & 1);
        const uint32_t a_addr = smem_base + s * STAGE + wg * (64 * BK * 2);
        const uint32_t b_addr = smem_base + s * STAGE + A_BYTES;
        wgmma_fence();
#pragma unroll
        for (int k = 0; k < BK / 16; ++k) {
            uint64_t da = make_desc(a_addr + k * 32, 16, 1024);
            uint64_t db = make_desc(b_addr + k * 2048, BOX_BYTES, 1024);
            wgmma_m64n256k16(acc, da, db, (it | k) != 0);
        }
        wgmma_commit();
        if (it > 0) {
            wgmma_wait<1>();
            if (leader) {
                mbar_arrive_cluster(empty_bar + 8 * ((it - 1) % STAGES), 0);
                mbar_arrive_cluster(empty_bar + 8 * ((it - 1) % STAGES), 1);
            }
        }
    }
    wgmma_wait<0>();
}

template <int STAGES, bool PDL_WAIT, typename Hook>
__device__ __forceinline__ void mainloop_producer(uint32_t smem_base, uint32_t full_bar, uint32_t empty_bar,
                                                  const CUtensorMap* tmA, const CUtensorMap* tmB, int a_k0, int a_row,
                                                  int b_col, int b_k0, uint32_t crank, Hook hook) {
    for (int it = 0; it < KT; ++it) {
        const int s = it % STAGES;
        mbar_wait(empty_bar + 8 * s, ((it / STAGES) & 1) ^ 1);
        const uint32_t st = smem_base + s * STAGE;
        mbar_expect_tx(full_bar + 8 * s, STAGE);
#pragma unroll
        for (int jj = 0; jj < 2; ++jj) {
            const int j = crank * 2 + jj;
            tma_load_2d_mc(st + A_BYTES + j * BOX_BYTES, tmB, full_bar + 8 * s, b_col + j * 64, b_k0 + it * BK,
                           (uint16_t)3);
        }
        if (PDL_WAIT && it == 0) asm volatile("griddepcontrol.wait;" ::: "memory");
        tma_load_2d(st, tmA, full_bar + 8 * s, a_k0 + it * BK, a_row);
        hook(it);
    }
}

__global__ void __cluster_dims__(2, 1, 1) __launch_bounds__(NTHREADS, 1)
qproj_attn_kernel(const __grid_constant__ CUtensorMap tmX0, const __grid_constant__ CUtensorMap tmX1,
                  const __grid_constant__ CUtensorMap tmW0, const __grid_constant__ CUtensorMap tmW1,
                  const __grid_constant__ CUtensorMap tmK0, const __grid_constant__ CUtensorMap tmK1,
                  const __grid_constant__ CUtensorMap tmV0, const __grid_constant__ CUtensorMap tmV1,
                  const __grid_constant__ CUtensorMap tmOst) {
    extern __shared__ uint8_t smem_raw[];
    const uint32_t smem_base = (smem_u32(smem_raw) + 1023) & ~1023u;
    const uint32_t full_bar = smem_base + K1_BAR_OFF;
    const uint32_t empty_bar = full_bar + 8 * K1_STAGES;
    const uint32_t k_bar = empty_bar + 8 * K1_STAGES;
    const uint32_t k_base = smem_base + K1_K_OFF;

    const int idx = blockIdx.x;
    const int blk = idx >> 6;
    const int nt = (idx & 63) >> 2;
    const int mt = idx & 3;
    const uint32_t crank = idx & 1;
    const int warp = threadIdx.x >> 5;
    const int lane = threadIdx.x & 31;

    if (threadIdx.x == 0) {
        for (int s = 0; s < K1_STAGES; ++s) {
            mbar_init(full_bar + 8 * s, 1);
            mbar_init(empty_bar + 8 * s, 4);
        }
        mbar_init(k_bar, 1);
        asm volatile("fence.mbarrier_init.release.cluster;" ::: "memory");
    }
    __syncthreads();
    STAMP(0, 0);
    cluster_sync_all();
    STAMP(0, 1);
    asm volatile("griddepcontrol.launch_dependents;" ::: "memory");

    if (warp >= 8) {
        if (warp == 8 && lane == 0) {
            const CUtensorMap* tmK = blk ? &tmK1 : &tmK0;
            const CUtensorMap* tmV = blk ? &tmV1 : &tmV0;
            mbar_expect_tx(k_bar, 8 * BOX_BYTES);
            mainloop_producer<K1_STAGES, false>(
                smem_base, full_bar, empty_bar, blk ? &tmX1 : &tmX0, blk ? &tmW1 : &tmW0, 0, mt * BM, nt * BN, 0, crank,
                [&](int it) {
                    const int e = it - 2;
                    if (e >= 0 && e < 8)
                        tma_load_2d(k_base + e * BOX_BYTES, tmK, k_bar, (e & 1) * 64,
                                    ((mt * 4 + (e >> 1)) * 32 + nt * 2) * 32);
                });
            for (int t = 0; t < 2; ++t) {
                const int it = KT + t, s = it % K1_STAGES;
                mbar_wait(empty_bar + 8 * s, ((it / K1_STAGES) & 1) ^ 1);
                const int nbox = t ? 2 : 6;
                mbar_expect_tx(full_bar + 8 * s, nbox * BOX_BYTES);
                for (int j = 0; j < nbox; ++j) {
                    const int e = t * 6 + j;
                    tma_load_2d(smem_base + STAGE + e * BOX_BYTES, tmV, full_bar + 8 * s, (e & 1) * 64,
                                ((mt * 4 + (e >> 1)) * 32 + nt * 2) * 32);
                }
            }
        }
    } else {
        const int wg = warp >> 2;
        const bool leader = (threadIdx.x & 127) == 0;
        float acc[128];
        mainloop_consumer<K1_STAGES>(acc, smem_base, full_bar, empty_bar, wg, leader);

        STAMP(0, 2);
        uint32_t qf[64];
#pragma unroll
        for (int i = 0; i < 64; ++i) qf[i] = pack_bf16(acc[2 * i], acc[2 * i + 1]);

        mbar_wait(k_bar, 0);
        asm volatile("bar.sync 3, 256;" ::: "memory");
        STAMP(0, 3);
        const int bl = wg * 2 + ((warp & 3) >> 1);
        const uint32_t kbase = k_base + (bl * 2) * BOX_BYTES;
        const uint32_t vbase = smem_base + STAGE + (bl * 2) * BOX_BYTES;
        const int orow = wg * 64 + (warp & 3) * 16 + (lane & 7) + ((lane >> 3) & 1) * 8;
        const uint32_t ost = smem_base + orow * 128;

        float sc[2][4][4];
#pragma unroll
        for (int hh = 0; hh < 2; ++hh)
#pragma unroll
            for (int n = 0; n < 4; ++n)
#pragma unroll
                for (int c = 0; c < 4; ++c) sc[hh][n][c] = 0.f;
#pragma unroll
        for (int kk = 0; kk < 8; kk += 2) {
            const int chunk = 2 * kk + (lane >> 3);
            const int half = chunk >> 3, c8 = chunk & 7;
            uint32_t kb[2][4][4];
#pragma unroll
            for (int hh = 0; hh < 2; ++hh)
#pragma unroll
                for (int n = 0; n < 4; ++n) {
                    const int r = hh * 32 + n * 8 + (lane & 7);
                    ldsm_x4(kbase + half * BOX_BYTES + r * 128 + ((c8 ^ (r & 7)) << 4), kb[hh][n][0], kb[hh][n][1],
                            kb[hh][n][2], kb[hh][n][3]);
                }
#pragma unroll
            for (int u = 0; u < 2; ++u)
#pragma unroll
                for (int hh = 0; hh < 2; ++hh)
#pragma unroll
                    for (int n = 0; n < 4; ++n) {
                        const int q0 = hh * 32 + (kk + u) * 4;
                        mma_bf16(sc[hh][n], qf[q0 + 0], qf[q0 + 1], qf[q0 + 2], qf[q0 + 3], kb[hh][n][2 * u],
                                 kb[hh][n][2 * u + 1]);
                    }
        }
        uint32_t pf[2][2][4];
#pragma unroll
        for (int hh = 0; hh < 2; ++hh) {
            const float scale = 0.08838834764831845f;
            float m0 = -INFINITY, m1 = -INFINITY;
#pragma unroll
            for (int n = 0; n < 4; ++n) {
#pragma unroll
                for (int c = 0; c < 4; ++c) sc[hh][n][c] = bf16_round(bf16_round(sc[hh][n][c]) * scale);
                m0 = fmaxf(m0, fmaxf(sc[hh][n][0], sc[hh][n][1]));
                m1 = fmaxf(m1, fmaxf(sc[hh][n][2], sc[hh][n][3]));
            }
            m0 = fmaxf(m0, __shfl_xor_sync(0xffffffffu, m0, 1));
            m1 = fmaxf(m1, __shfl_xor_sync(0xffffffffu, m1, 1));
            m0 = fmaxf(m0, __shfl_xor_sync(0xffffffffu, m0, 2));
            m1 = fmaxf(m1, __shfl_xor_sync(0xffffffffu, m1, 2));
            float s0 = 0.f, s1 = 0.f;
#pragma unroll
            for (int n = 0; n < 4; ++n) {
                sc[hh][n][0] = __expf(sc[hh][n][0] - m0);
                sc[hh][n][1] = __expf(sc[hh][n][1] - m0);
                sc[hh][n][2] = __expf(sc[hh][n][2] - m1);
                sc[hh][n][3] = __expf(sc[hh][n][3] - m1);
                s0 += sc[hh][n][0] + sc[hh][n][1];
                s1 += sc[hh][n][2] + sc[hh][n][3];
            }
            s0 += __shfl_xor_sync(0xffffffffu, s0, 1);
            s1 += __shfl_xor_sync(0xffffffffu, s1, 1);
            s0 += __shfl_xor_sync(0xffffffffu, s0, 2);
            s1 += __shfl_xor_sync(0xffffffffu, s1, 2);
            const float i0 = 1.f / s0, i1 = 1.f / s1;
#pragma unroll
            for (int kk = 0; kk < 2; ++kk) {
                pf[hh][kk][0] = pack_bf16(sc[hh][2 * kk][0] * i0, sc[hh][2 * kk][1] * i0);
                pf[hh][kk][1] = pack_bf16(sc[hh][2 * kk][2] * i1, sc[hh][2 * kk][3] * i1);
                pf[hh][kk][2] = pack_bf16(sc[hh][2 * kk + 1][0] * i0, sc[hh][2 * kk + 1][1] * i0);
                pf[hh][kk][3] = pack_bf16(sc[hh][2 * kk + 1][2] * i1, sc[hh][2 * kk + 1][3] * i1);
            }
        }
        STAMP(0, 6);
        mbar_wait(full_bar + 8 * (KT % K1_STAGES), (KT / K1_STAGES) & 1);
        mbar_wait(full_bar + 8 * ((KT + 1) % K1_STAGES), ((KT + 1) / K1_STAGES) & 1);
#pragma unroll
        for (int hb = 0; hb < 4; ++hb) {
            const int hh = hb >> 1, half = hb & 1;
            const int r = hh * 32 + lane;
            const uint32_t addr = vbase + half * BOX_BYTES + r * 128;
            uint32_t vb[8][4];
#pragma unroll
            for (int c = 0; c < 8; ++c)
                ldsm_x4_t(addr + ((c ^ (r & 7)) << 4), vb[c][0], vb[c][1], vb[c][2], vb[c][3]);
            float oc[8][4];
#pragma unroll
            for (int c = 0; c < 8; ++c) {
                oc[c][0] = oc[c][1] = oc[c][2] = oc[c][3] = 0.f;
                mma_bf16(oc[c], pf[hh][0][0], pf[hh][0][1], pf[hh][0][2], pf[hh][0][3], vb[c][0], vb[c][1]);
            }
#pragma unroll
            for (int c = 0; c < 8; ++c)
                mma_bf16(oc[c], pf[hh][1][0], pf[hh][1][1], pf[hh][1][2], pf[hh][1][3], vb[c][2], vb[c][3]);
#pragma unroll
            for (int c = 0; c < 8; c += 2) {
                const int cn = c + (lane >> 4);
                stsm_x4(ost + (hb == 3 ? 7 : hb) * 16384 + ((cn ^ (orow & 7)) << 4), pack_bf16(oc[c][0], oc[c][1]),
                        pack_bf16(oc[c][2], oc[c][3]), pack_bf16(oc[c + 1][0], oc[c + 1][1]),
                        pack_bf16(oc[c + 1][2], oc[c + 1][3]));
            }
            if (hb == 1 || hb == 3) {
                fence_async_smem();
                wg_bar(wg);
                if (leader) {
                    tma_store_2d(&tmOst, smem_base + (hb - 1) * 16384 + wg * 8192, nt * 256 + (hb - 1) * 64,
                                 blk * 512 + mt * BM + wg * 64);
                    tma_store_2d(&tmOst, smem_base + (hb == 3 ? 7 : hb) * 16384 + wg * 8192, nt * 256 + hb * 64,
                                 blk * 512 + mt * BM + wg * 64);
                    asm volatile("cp.async.bulk.commit_group;" ::: "memory");
                }
            }
        }
        STAMP(0, 5);
        if (leader) asm volatile("cp.async.bulk.wait_group 0;" ::: "memory");
    }
    STAMP(0, 4);
    cluster_sync_all();
}

__device__ float4 g_red[32 * 4 * 4 * 8 * 256];
__device__ unsigned int g_flag[32 * 4 * 8];

__global__ void __cluster_dims__(2, 1, 1) __launch_bounds__(NTHREADS, 1)
oproj_kernel(const __grid_constant__ CUtensorMap tmO, const __grid_constant__ CUtensorMap tmW0,
             const __grid_constant__ CUtensorMap tmW1, const __grid_constant__ CUtensorMap tmOut) {
    extern __shared__ uint8_t smem_raw[];
    const uint32_t smem_base = (smem_u32(smem_raw) + 1023) & ~1023u;
    const uint32_t full_bar = smem_base + K2_BAR_OFF;
    const uint32_t empty_bar = full_bar + 8 * K2_STAGES;

    const int idx = blockIdx.x;
    const int blk = idx >> 6;
    const int ks = (idx >> 4) & 3;
    const int nt = (idx >> 2) & 3;
    const int mt = idx & 3;
    const uint32_t crank = idx & 1;
    const int tile = blk * 16 + mt * 4 + nt;
    const int warp = threadIdx.x >> 5;

    if (threadIdx.x == 0) {
        for (int s = 0; s < K2_STAGES; ++s) {
            mbar_init(full_bar + 8 * s, 1);
            mbar_init(empty_bar + 8 * s, 4);
        }
        asm volatile("fence.mbarrier_init.release.cluster;" ::: "memory");
    }
    __syncthreads();
    STAMP(1, 0);
    cluster_sync_all();
    STAMP(1, 1);

    if (warp >= 8) {
        if (warp == 8 && (threadIdx.x & 31) == 0) {
            mainloop_producer<K2_STAGES, true>(smem_base, full_bar, empty_bar, &tmO, blk ? &tmW1 : &tmW0, ks * 1024,
                                           blk * 512 + mt * BM, nt * BN, ks * 1024, crank, [](int) {});
        }
    } else {
        const int wg = warp >> 2;
        const bool leader = (threadIdx.x & 127) == 0;
        float acc[128];
        mainloop_consumer<K2_STAGES>(acc, smem_base, full_bar, empty_bar, wg, leader);

        STAMP(1, 2);
        const int tid = threadIdx.x;
#pragma unroll
        for (int j = 0; j < 4; ++j) {
            if (j != ks) {
                float4* dst = g_red + ((size_t)((tile * 4 + j) * 4 + ks) * 8) * 256 + tid;
#pragma unroll
                for (int i = 0; i < 8; ++i)
                    __stcg(dst + i * 256, make_float4(acc[j * 32 + i * 4 + 0], acc[j * 32 + i * 4 + 1],
                                                      acc[j * 32 + i * 4 + 2], acc[j * 32 + i * 4 + 3]));
            }
        }
        STAMP(1, 5);
        __threadfence();
        __syncwarp();
        STAMP(1, 6);
        if ((tid & 31) == 0) {
#pragma unroll
            for (int j = 0; j < 4; ++j)
                if (j != ks) atomicAdd(&g_flag[(tile * 4 + j) * 8 + warp], 1u);
            volatile unsigned int* f = &g_flag[(tile * 4 + ks) * 8 + warp];
            unsigned int spins = 0;
            while (*f < 3u && ++spins < (1u << 26)) { }
            *f = 0;
            __threadfence();
        }
        __syncwarp();
        STAMP(1, 3);
        const int lane = tid & 31;
        const int orow = wg * 64 + (warp & 3) * 16 + (lane & 7) + ((lane >> 3) & 1) * 8;
        const uint32_t ost = smem_base + orow * 128;
#pragma unroll
        for (int j = 0; j < 4; ++j) {
            if (j == ks) {
#pragma unroll
                for (int i = 0; i < 8; i += 2) {
                    uint32_t pk[4];
#pragma unroll
                    for (int u = 0; u < 2; ++u) {
                        float v0 = acc[j * 32 + (i + u) * 4 + 0], v1 = acc[j * 32 + (i + u) * 4 + 1];
                        float v2 = acc[j * 32 + (i + u) * 4 + 2], v3 = acc[j * 32 + (i + u) * 4 + 3];
#pragma unroll
                        for (int sl = 0; sl < 4; ++sl) {
                            if (sl != j) {
                                float4 r = __ldcg(g_red + ((size_t)((tile * 4 + j) * 4 + sl) * 8 + i + u) * 256 + tid);
                                v0 += r.x; v1 += r.y; v2 += r.z; v3 += r.w;
                            }
                        }
                        pk[u * 2 + 0] = pack_bf16(v0, v1);
                        pk[u * 2 + 1] = pack_bf16(v2, v3);
                    }
                    const int cn = i + (lane >> 4);
                    stsm_x4(ost + ((cn ^ (orow & 7)) << 4), pk[0], pk[1], pk[2], pk[3]);
                }
            }
        }
        fence_async_smem();
        wg_bar(wg);
        if (leader) {
            tma_store_2d(&tmOut, smem_base + wg * 8192, blk * 1024 + nt * 256 + ks * 64, mt * BM + wg * 64);
            tma_store_commit_wait();
        }
    }
    STAMP(1, 4);
    cluster_sync_all();
}

typedef CUresult (*EncodeFn)(CUtensorMap*, CUtensorMapDataType, cuuint32_t, void*, const cuuint64_t*,
                             const cuuint64_t*, const cuuint32_t*, const cuuint32_t*, CUtensorMapInterleave,
                             CUtensorMapSwizzle, CUtensorMapL2promotion, CUtensorMapFloatOOBfill);

EncodeFn get_encode() {
    static EncodeFn fn = nullptr;
    if (!fn) {
        void* p = nullptr;
        cudaDriverEntryPointQueryResult qres;
        cudaGetDriverEntryPoint("cuTensorMapEncodeTiled", &p, cudaEnableDefault, &qres);
        fn = (EncodeFn)p;
    }
    return fn;
}

CUtensorMap make_map(const void* ptr, uint64_t inner, uint64_t outer, uint32_t box_inner, uint32_t box_outer,
                     CUtensorMapSwizzle swz = CU_TENSOR_MAP_SWIZZLE_128B) {
    CUtensorMap m;
    cuuint64_t dims[2] = {inner, outer};
    cuuint64_t strides[1] = {inner * 2};
    cuuint32_t box[2] = {box_inner, box_outer};
    cuuint32_t estr[2] = {1, 1};
    get_encode()(&m, CU_TENSOR_MAP_DATA_TYPE_BFLOAT16, 2, const_cast<void*>(ptr), dims, strides, box, estr,
                 CU_TENSOR_MAP_INTERLEAVE_NONE, swz, CU_TENSOR_MAP_L2_PROMOTION_L2_256B,
                 CU_TENSOR_MAP_FLOAT_OOB_FILL_NONE);
    return m;
}

}

extern "C" void kernel_launch(void* const* d_in, const int* in_sizes, int n_in, void* d_out, int out_size) {
    (void)in_sizes; (void)n_in; (void)out_size;
    void* o_scratch = nullptr;
    cudaGetSymbolAddress(&o_scratch, g_o);

    CUtensorMap tmX[2], tmWq[2], tmK[2], tmV[2], tmWo[2];
    for (int b = 0; b < 2; ++b) {
        tmX[b] = make_map(d_in[b * 5 + 0], 1024, 512, 64, 128);
        tmK[b] = make_map(d_in[b * 5 + 1], 128, 16384, 64, 64);
        tmV[b] = make_map(d_in[b * 5 + 2], 128, 16384, 64, 64);
        tmWq[b] = make_map(d_in[b * 5 + 3], 4096, 1024, 64, 64);
        tmWo[b] = make_map(d_in[b * 5 + 4], 1024, 4096, 64, 64);
    }
    CUtensorMap tmO = make_map(o_scratch, 4096, 1024, 64, 128);
    CUtensorMap tmOst = make_map(o_scratch, 4096, 1024, 64, 64);
    CUtensorMap tmOut = make_map(d_out, 2048, 512, 64, 64);

    static bool attr_done = false;
    if (!attr_done) {
        cudaFuncSetAttribute(qproj_attn_kernel, cudaFuncAttributeMaxDynamicSharedMemorySize, K1_SMEM);
        cudaFuncSetAttribute(oproj_kernel, cudaFuncAttributeMaxDynamicSharedMemorySize, K2_SMEM);
        attr_done = true;
    }
    qproj_attn_kernel<<<128, NTHREADS, K1_SMEM>>>(tmX[0], tmX[1], tmWq[0], tmWq[1], tmK[0], tmK[1], tmV[0], tmV[1],
                                                  tmOst);
    cudaLaunchConfig_t cfg = {};
    cfg.gridDim = dim3(128);
    cfg.blockDim = dim3(NTHREADS);
    cfg.dynamicSmemBytes = K2_SMEM;
    cfg.stream = cudaStreamPerThread;
    cudaLaunchAttribute at[1];
    at[0].id = cudaLaunchAttributeProgrammaticStreamSerialization;
    at[0].val.programmaticStreamSerializationAllowed = 1;
    cfg.attrs = at;
    cfg.numAttrs = 1;
    cudaLaunchKernelEx(&cfg, oproj_kernel, tmO, tmWo[0], tmWo[1], tmOut);
}
```
